```python
import torch

def _softmax(x, axis=-1):
    return torch.softmax(x, dim=axis)

def _gelu(x):
    return torch.nn.functional.gelu(x, approximate='tanh')

def _silu(x):
    return torch.nn.functional.silu(x)

def _sigmoid(x):
    return torch.sigmoid(x)

def _layernorm(x, axis=-1, eps=1e-05):
    m = x.mean(dim=axis, keepdim=True)
    v = x.var(dim=axis, keepdim=True, unbiased=False)
    return (x - m) / torch.sqrt(v + eps)

def _scatter_add(tgt, idx, src, axis=0):
    return tgt.clone().index_add_(axis, idx, src)

def _segment_sum(src, seg, n):
    out = torch.zeros((n,) + src.shape[1:], dtype=src.dtype)
    return out.index_add_(0, seg, src)

def _pad(x, pw):
    flat = tuple((v for pair in reversed(pw) for v in pair))
    return torch.nn.functional.pad(x, flat)
kernel_name = 'gated_mix__sliding_block__memory_aug_recurrent_mem_tr__prompt'

def setup_inputs():

    _w = lambda a: (lambda t: t.to(torch.bfloat16) if t.is_floating_point() else t)(torch.as_tensor(a))

    def _A_setup():
        B, S, D = (1, 2048, 448)
        return {'x': _w((lambda *s: torch.randn(*s, dtype=torch.bfloat16) * 0.05)(B, S, D)), 'wqkv': _w((lambda *s: torch.randn(*s, dtype=torch.bfloat16) * 1.6)(D, 3 * D)), 'wo': _w((lambda *s: torch.randn(*s, dtype=torch.bfloat16) * 0.05)(D, D))}
    _A_in = _A_setup()

    def _B_setup():
        B, S, Dm = (1, 2048, 448)
        H, Dh = (16, 256)
        M, seg = (8, 32)
        seg = min(seg, S)
        S = S // seg * seg
        return {'x': _w((lambda *s: torch.randn(*s, dtype=torch.bfloat16) * 0.05)(B, S, Dm)), 'mem0': _w((lambda *s: torch.randn(*s, dtype=torch.bfloat16) * 1.6)(B, M, Dm)), 'Wq': _w((lambda *s: torch.randn(*s, dtype=torch.bfloat16) * 0.8)(Dm, H, Dh) * Dm ** (-0.5)), 'Wk': _w((lambda *s: torch.randn(*s, dtype=torch.bfloat16) * 0.8)(Dm, H, Dh) * Dm ** (-0.5)), 'Wv': _w((lambda *s: torch.randn(*s, dtype=torch.bfloat16) * 1.6)(Dm, H, Dh) * Dm ** (-0.5)), 'Wo': _w((lambda *s: torch.randn(*s, dtype=torch.bfloat16) * 1.6)(H, Dh, Dm) * (H * Dh) ** (-0.5)), 'seg_len': seg}
    _B_in = _B_setup()
    return {'A_x': _A_in['x'], 'A_wqkv': _A_in['wqkv'], 'A_wo': _A_in['wo'], 'B_x': _B_in['x'], 'B_mem0': _B_in['mem0'], 'B_Wq': _B_in['Wq'], 'B_Wk': _B_in['Wk'], 'B_Wv': _B_in['Wv'], 'B_Wo': _B_in['Wo'], 'B_seg_len': _B_in['seg_len'], 'gate_w': _w((lambda *s: torch.randn(*s, dtype=torch.bfloat16) * 0.05)(448) * 16.0)}

def reference(A_x, A_wqkv, A_wo, B_x, B_mem0, B_Wq, B_Wk, B_Wv, B_Wo, B_seg_len, gate_w):

    def _A_ref(x, wqkv, wo):
        B, S, D = x.shape
        H = 16
        Dh = D // H
        W = 256
        qkv = (lambda x, *d: x.permute(*d))((x @ wqkv).reshape(B, S, 3, H, Dh), 2, 0, 3, 1, 4)
        q, k, v = (qkv[0], qkv[1], qkv[2])
        scores = torch.einsum('bhqd,bhkd->bhqk', q, k) * Dh ** (-0.5)
        idx = torch.arange(S)
        mask = (idx[:, None] - idx[None, :] >= 0) & (idx[:, None] - idx[None, :] < W)
        scores = torch.where(mask[None, None], scores, -1000000000.0)
        p = _softmax(scores, axis=-1)
        o = torch.einsum('bhqk,bhkd->bhqd', p, v)
        return (lambda x, *d: x.permute(*d))(o, 0, 2, 1, 3).reshape(B, S, D) @ wo

    def _B_ref(x, mem0, Wq, Wk, Wv, Wo, seg_len):
        B, S, Dm = x.shape
        H, Dh = (Wq.shape[1], Wq.shape[2])
        M = mem0.shape[1]
        scale = Dh ** (-0.5)
        n_seg = S // seg_len
        L = M + seg_len
        idx = torch.arange(L)
        mask = (idx[:, None] < M) | (idx[:, None] >= idx[None, :])
        mem = mem0
        outs = []
        for s in range(n_seg):
            xs = x[:, s * seg_len:(s + 1) * seg_len, :].clone()
            h = torch.concatenate([mem, xs], axis=1)
            q = torch.einsum('btd,dhe->bhte', h, Wq)
            k = torch.einsum('btd,dhe->bhte', h, Wk)
            v = torch.einsum('btd,dhe->bhte', h, Wv)
            scores = torch.einsum('bhqe,bhke->bhqk', q, k) * scale
            scores = torch.where(mask[None, None], scores, -1000000000.0)
            p = _softmax(scores, axis=-1)
            o = torch.einsum('bhqk,bhke->bhqe', p, v)
            o = torch.einsum('bhte,hed->btd', o, Wo)
            mem = o[:, :M, :].clone()
            outs.append(o[:, M:, :])
        return torch.concatenate(outs, axis=1)
    x = A_x
    g = _sigmoid((x * gate_w).sum(-1, keepdims=True))
    a = _A_ref(x, A_wqkv, A_wo)
    b = _B_ref(x, B_mem0, B_Wq, B_Wk, B_Wv, B_Wo, B_seg_len)
    return g * a + (1 - g) * b
```

```cpp
#include <cuda_runtime.h>
#include <cuda_bf16.h>
#include <cuda.h>
#include <stdint.h>

typedef __nv_bfloat16 bf16;

constexpr int SEQ = 2048;
constexpr int DM = 448;
constexpr int NH = 16;
constexpr int DHB = 256;
constexpr int NSEG = 64;
constexpr int SEGL = 32;
constexpr int NMEM = 8;
constexpr int NSL = 7;
constexpr uint32_t SENT = 0xFFFFFFFFu;
constexpr int SPIN_LIMIT = 1 << 22;

__device__ __forceinline__ uint32_t smem_u32(const void* p) { return (uint32_t)__cvta_generic_to_shared(p); }
__device__ __forceinline__ uint32_t mapa(uint32_t a, uint32_t r) {
    uint32_t o; asm("mapa.shared::cluster.u32 %0, %1, %2;" : "=r"(o) : "r"(a), "r"(r)); return o;
}
__device__ __forceinline__ void mbar_init(uint32_t a, uint32_t c) {
    asm volatile("mbarrier.init.shared::cta.b64 [%0], %1;" :: "r"(a), "r"(c) : "memory");
}
__device__ __forceinline__ void mbar_expect(uint32_t a, uint32_t tx) {
    asm volatile("mbarrier.arrive.expect_tx.shared::cta.b64 _, [%0], %1;" :: "r"(a), "r"(tx) : "memory");
}
__device__ __forceinline__ void mbar_arrive(uint32_t a) {
    asm volatile("mbarrier.arrive.shared::cta.b64 _, [%0];" :: "r"(a) : "memory");
}
__device__ __forceinline__ void mbar_arrive_if(uint32_t a, bool cond) {
    asm volatile("{\n.reg .pred p;\nsetp.ne.u32 p, %1, 0;\n@p mbarrier.arrive.shared::cta.b64 _, [%0];\n}" :: "r"(a), "r"((uint32_t)cond) : "memory");
}
__device__ __forceinline__ bool mbar_try(uint32_t a, uint32_t ph) {
    uint32_t ok;
    asm volatile("{\n.reg .pred p;\nmbarrier.try_wait.parity.shared::cta.b64 p, [%1], %2;\nselp.u32 %0, 1, 0, p;\n}"
                 : "=r"(ok) : "r"(a), "r"(ph) : "memory");
    return ok;
}
__device__ __forceinline__ bool mbar_test(uint32_t a, uint32_t ph) {
    uint32_t ok;
    asm volatile("{\n.reg .pred p;\nmbarrier.test_wait.parity.shared::cta.b64 p, [%1], %2;\nselp.u32 %0, 1, 0, p;\n}"
                 : "=r"(ok) : "r"(a), "r"(ph) : "memory");
    return ok;
}
__device__ __forceinline__ void die() { asm volatile("st.global.u32 [%0], %1;" :: "l"((uint64_t)0), "r"(0u) : "memory"); }
__device__ __forceinline__ void mbar_spin(uint32_t a, uint32_t ph) {
    int c = 0;
    while (!mbar_test(a, ph)) { if (++c > (SPIN_LIMIT << 5)) { die(); break; } }
}
__device__ __forceinline__ void mbar_wait(uint32_t a, uint32_t ph) {
    int c = 0;
    while (!mbar_try(a, ph)) { if (++c > SPIN_LIMIT) { die(); break; } }
}
__device__ __forceinline__ void bar_sync(int id, int n) { asm volatile("bar.sync %0, %1;" :: "r"(id), "r"(n) : "memory"); }
__device__ __forceinline__ void bar_arrive(int id, int n) { asm volatile("bar.arrive %0, %1;" :: "r"(id), "r"(n) : "memory"); }
__device__ __forceinline__ void fence_proxy_async() { asm volatile("fence.proxy.async.shared::cta;" ::: "memory"); }
__device__ __forceinline__ void fence_proxy_async_all() { asm volatile("fence.proxy.async.global;" ::: "memory"); }
__device__ __forceinline__ void cluster_sync_all() {
    asm volatile("barrier.cluster.arrive.release.aligned;\nbarrier.cluster.wait.acquire.aligned;" ::: "memory");
}
__device__ __forceinline__ void st_async_v4(uint32_t a, uint32_t x, uint32_t y, uint32_t z, uint32_t w, uint32_t mb) {
    asm volatile("st.async.weak.shared::cluster.mbarrier::complete_tx::bytes.v4.b32 [%0], {%1,%2,%3,%4}, [%5];"
                 :: "r"(a), "r"(x), "r"(y), "r"(z), "r"(w), "r"(mb) : "memory");
}
__device__ __forceinline__ uint4 ld_relaxed_v4(const void* p) {
    uint4 v; asm volatile("ld.relaxed.gpu.global.v4.u32 {%0,%1,%2,%3}, [%4];" : "=r"(v.x), "=r"(v.y), "=r"(v.z), "=r"(v.w) : "l"(p) : "memory"); return v;
}
__device__ __forceinline__ uint2 ld_relaxed_v2(const void* p) {
    uint2 v; asm volatile("ld.relaxed.gpu.global.v2.u32 {%0,%1}, [%2];" : "=r"(v.x), "=r"(v.y) : "l"(p) : "memory"); return v;
}
__device__ __forceinline__ uint32_t ld_acquire(const void* p) {
    uint32_t v; asm volatile("ld.acquire.gpu.global.u32 %0, [%1];" : "=r"(v) : "l"(p) : "memory"); return v;
}
__device__ __forceinline__ uint32_t ld_relaxed(const void* p) {
    uint32_t v; asm volatile("ld.relaxed.gpu.global.u32 %0, [%1];" : "=r"(v) : "l"(p) : "memory"); return v;
}
__device__ __forceinline__ void st_relaxed_v4(void* p, uint32_t x, uint32_t y, uint32_t z, uint32_t w) {
    asm volatile("st.relaxed.gpu.global.v4.u32 [%0], {%1,%2,%3,%4};" :: "l"(p), "r"(x), "r"(y), "r"(z), "r"(w) : "memory");
}
__device__ __forceinline__ void st_relaxed_v2(void* p, uint32_t x, uint32_t y) {
    asm volatile("st.relaxed.gpu.global.v2.u32 [%0], {%1,%2};" :: "l"(p), "r"(x), "r"(y) : "memory");
}
__device__ __forceinline__ void st_relaxed(void* p, uint32_t v) {
    asm volatile("st.relaxed.gpu.global.u32 [%0], %1;" :: "l"(p), "r"(v) : "memory");
}
__device__ __forceinline__ uint32_t pack_bf16(float lo, float hi) {
    uint32_t r; asm("cvt.rn.bf16x2.f32 %0, %1, %2;" : "=r"(r) : "f"(hi), "f"(lo)); return r;
}
__device__ __forceinline__ float bf_lo(uint32_t w) { return __uint_as_float(w << 16); }
__device__ __forceinline__ float bf_hi(uint32_t w) { return __uint_as_float(w & 0xffff0000u); }
__device__ __forceinline__ float ex2(float x) { float y; asm("ex2.approx.ftz.f32 %0, %1;" : "=f"(y) : "f"(x)); return y; }
__device__ __forceinline__ float rcp_approx(float x) { float y; asm("rcp.approx.ftz.f32 %0, %1;" : "=f"(y) : "f"(x)); return y; }
__device__ __forceinline__ uint32_t movmatrix_t(uint32_t a) {
    uint32_t d; asm("movmatrix.sync.aligned.m8n8.trans.b16 %0, %1;" : "=r"(d) : "r"(a)); return d;
}
__device__ __forceinline__ void ldsm_x4(uint32_t& r0, uint32_t& r1, uint32_t& r2, uint32_t& r3, uint32_t addr) {
    asm volatile("ldmatrix.sync.aligned.m8n8.x4.shared.b16 {%0,%1,%2,%3}, [%4];" : "=r"(r0), "=r"(r1), "=r"(r2), "=r"(r3) : "r"(addr) : "memory");
}
__device__ __forceinline__ void ldsm_x4_t(uint32_t& r0, uint32_t& r1, uint32_t& r2, uint32_t& r3, uint32_t addr) {
    asm volatile("ldmatrix.sync.aligned.m8n8.x4.trans.shared.b16 {%0,%1,%2,%3}, [%4];" : "=r"(r0), "=r"(r1), "=r"(r2), "=r"(r3) : "r"(addr) : "memory");
}
__device__ __forceinline__ void ldsm_x2(uint32_t& r0, uint32_t& r1, uint32_t addr) {
    asm volatile("ldmatrix.sync.aligned.m8n8.x2.shared.b16 {%0,%1}, [%2];" : "=r"(r0), "=r"(r1) : "r"(addr) : "memory");
}
__device__ __forceinline__ void stsm_x4(uint32_t addr, uint32_t r0, uint32_t r1, uint32_t r2, uint32_t r3) {
    asm volatile("stmatrix.sync.aligned.m8n8.x4.shared.b16 [%0], {%1,%2,%3,%4};" :: "r"(addr), "r"(r0), "r"(r1), "r"(r2), "r"(r3) : "memory");
}
__device__ __forceinline__ void stsm_x4_t(uint32_t addr, uint32_t r0, uint32_t r1, uint32_t r2, uint32_t r3) {
    asm volatile("stmatrix.sync.aligned.m8n8.x4.trans.shared.b16 [%0], {%1,%2,%3,%4};" :: "r"(addr), "r"(r0), "r"(r1), "r"(r2), "r"(r3) : "memory");
}
__device__ __forceinline__ void mma16816(float (&d)[4], uint32_t a0, uint32_t a1, uint32_t a2, uint32_t a3, uint32_t b0, uint32_t b1) {
    asm("mma.sync.aligned.m16n8k16.row.col.f32.bf16.bf16.f32 {%0,%1,%2,%3}, {%4,%5,%6,%7}, {%8,%9}, {%0,%1,%2,%3};"
                 : "+f"(d[0]), "+f"(d[1]), "+f"(d[2]), "+f"(d[3]) : "r"(a0), "r"(a1), "r"(a2), "r"(a3), "r"(b0), "r"(b1));
}
__device__ __forceinline__ void mma16816v(float (&d)[4], uint32_t a0, uint32_t a1, uint32_t a2, uint32_t a3, uint32_t b0, uint32_t b1) {
    asm volatile("mma.sync.aligned.m16n8k16.row.col.f32.bf16.bf16.f32 {%0,%1,%2,%3}, {%4,%5,%6,%7}, {%8,%9}, {%0,%1,%2,%3};"
                 : "+f"(d[0]), "+f"(d[1]), "+f"(d[2]), "+f"(d[3]) : "r"(a0), "r"(a1), "r"(a2), "r"(a3), "r"(b0), "r"(b1));
}
__device__ __forceinline__ uint64_t desc_sw128(uint32_t addr) {
    return (uint64_t)((addr & 0x3FFFF) >> 4) | ((uint64_t)1 << 16) | ((uint64_t)64 << 32) | ((uint64_t)1 << 62);
}
__device__ __forceinline__ uint32_t desc_lo(uint32_t addr) { return __shfl_sync(0xffffffffu, ((addr & 0x3FFFF) >> 4) | (1u << 16), 0); }
__device__ __forceinline__ uint64_t desc_at(uint32_t lo, uint32_t byte_off) { return ((uint64_t)0x40000040u << 32) | (uint64_t)(lo + (byte_off >> 4)); }
__device__ __forceinline__ void wg_fence() { asm volatile("wgmma.fence.sync.aligned;" ::: "memory"); }
__device__ __forceinline__ void wg_commit() { asm volatile("wgmma.commit_group.sync.aligned;" ::: "memory"); }
template <int N> __device__ __forceinline__ void wg_wait() { asm volatile("wgmma.wait_group.sync.aligned %0;" :: "n"(N) : "memory"); }
__device__ __forceinline__ void wgmma_rs_n8(float (&d)[4], const uint32_t (&a)[4], uint64_t b, int sc) {
    asm volatile("{\n.reg .pred p;\nsetp.ne.b32 p, %9, 0;\n"
                 "wgmma.mma_async.sync.aligned.m64n8k16.f32.bf16.bf16 {%0,%1,%2,%3}, {%4,%5,%6,%7}, %8, p, 1, 1, 0;\n}"
                 : "+f"(d[0]), "+f"(d[1]), "+f"(d[2]), "+f"(d[3]) : "r"(a[0]), "r"(a[1]), "r"(a[2]), "r"(a[3]), "l"(b), "r"(sc));
}
__device__ __forceinline__ void wgmma_rs_n32(float (&d)[16], const uint32_t (&a)[4], uint64_t b, int sc) {
    asm volatile("{\n.reg .pred p;\nsetp.ne.b32 p, %21, 0;\n"
                 "wgmma.mma_async.sync.aligned.m64n32k16.f32.bf16.bf16 {%0,%1,%2,%3,%4,%5,%6,%7,%8,%9,%10,%11,%12,%13,%14,%15}, {%16,%17,%18,%19}, %20, p, 1, 1, 0;\n}"
                 : "+f"(d[0]), "+f"(d[1]), "+f"(d[2]), "+f"(d[3]), "+f"(d[4]), "+f"(d[5]), "+f"(d[6]), "+f"(d[7]),
                   "+f"(d[8]), "+f"(d[9]), "+f"(d[10]), "+f"(d[11]), "+f"(d[12]), "+f"(d[13]), "+f"(d[14]), "+f"(d[15])
                 : "r"(a[0]), "r"(a[1]), "r"(a[2]), "r"(a[3]), "l"(b), "r"(sc));
}
template <int TA>
__device__ __forceinline__ void wgmma_ss_n64(float (&d)[32], uint64_t a, uint64_t b, int sc) {
    asm volatile("{\n.reg .pred p;\nsetp.ne.b32 p, %34, 0;\n"
                 "wgmma.mma_async.sync.aligned.m64n64k16.f32.bf16.bf16 "
                 "{%0,%1,%2,%3,%4,%5,%6,%7,%8,%9,%10,%11,%12,%13,%14,%15,%16,%17,%18,%19,%20,%21,%22,%23,%24,%25,%26,%27,%28,%29,%30,%31}, %32, %33, p, 1, 1, %35, 0;\n}"
                 : "+f"(d[0]), "+f"(d[1]), "+f"(d[2]), "+f"(d[3]), "+f"(d[4]), "+f"(d[5]), "+f"(d[6]), "+f"(d[7]),
                   "+f"(d[8]), "+f"(d[9]), "+f"(d[10]), "+f"(d[11]), "+f"(d[12]), "+f"(d[13]), "+f"(d[14]), "+f"(d[15]),
                   "+f"(d[16]), "+f"(d[17]), "+f"(d[18]), "+f"(d[19]), "+f"(d[20]), "+f"(d[21]), "+f"(d[22]), "+f"(d[23]),
                   "+f"(d[24]), "+f"(d[25]), "+f"(d[26]), "+f"(d[27]), "+f"(d[28]), "+f"(d[29]), "+f"(d[30]), "+f"(d[31])
                 : "l"(a), "l"(b), "r"(sc), "n"(TA));
}
__device__ __forceinline__ void tma_2d(uint32_t dst, const CUtensorMap* tm, int c0, int c1, uint32_t bar) {
    asm volatile("cp.async.bulk.tensor.2d.shared::cluster.global.mbarrier::complete_tx::bytes [%0], [%1, {%3, %4}], [%2];"
                 :: "r"(dst), "l"(tm), "r"(bar), "r"(c0), "r"(c1) : "memory");
}
__device__ __forceinline__ void tma_3d(uint32_t dst, const CUtensorMap* tm, int c0, int c1, int c2, uint32_t bar) {
    asm volatile("cp.async.bulk.tensor.3d.shared::cluster.global.mbarrier::complete_tx::bytes [%0], [%1, {%3, %4, %5}], [%2];"
                 :: "r"(dst), "l"(tm), "r"(bar), "r"(c0), "r"(c1), "r"(c2) : "memory");
}
__device__ __forceinline__ void tma_3d_mc(uint32_t dst, const CUtensorMap* tm, int c0, int c1, int c2, uint32_t bar, uint16_t mask) {
    asm volatile("cp.async.bulk.tensor.3d.shared::cluster.global.mbarrier::complete_tx::bytes.multicast::cluster [%0], [%1, {%3, %4, %5}], [%2], %6;"
                 :: "r"(dst), "l"(tm), "r"(bar), "r"(c0), "r"(c1), "r"(c2), "h"(mask) : "memory");
}
__device__ __forceinline__ void bulk_mc(uint32_t dst, const void* src, uint32_t bytes, uint32_t bar, uint16_t mask) {
    asm volatile("cp.async.bulk.shared::cluster.global.mbarrier::complete_tx::bytes.multicast::cluster [%0], [%1], %2, [%3], %4;"
                 :: "r"(dst), "l"(src), "r"(bytes), "r"(bar), "h"(mask) : "memory");
}
__device__ __forceinline__ void bulk_ld(uint32_t dst, const void* src, uint32_t bytes, uint32_t bar) {
    asm volatile("cp.async.bulk.shared::cluster.global.mbarrier::complete_tx::bytes [%0], [%1], %2, [%3];"
                 :: "r"(dst), "l"(src), "r"(bytes), "r"(bar) : "memory");
}
template <int N> __device__ __forceinline__ void reg_inc() { asm volatile("setmaxnreg.inc.sync.aligned.u32 %0;" :: "n"(N)); }
template <int N> __device__ __forceinline__ void reg_dec() { asm volatile("setmaxnreg.dec.sync.aligned.u32 %0;" :: "n"(N)); }
__device__ __forceinline__ uint32_t clk32() { uint32_t c; asm volatile("mov.u32 %0, %%clock;" : "=r"(c)); return c; }
__device__ __forceinline__ void spin_clks(uint32_t n) { uint32_t t = clk32(); while (clk32() - t < n) {} }

#define TS(i) do {} while (0)
#define TSMAX(i) do {} while (0)

constexpr int R_CS = 16;
constexpr int R_CTAS = R_CS * NSL;
#define XEARLY 1
#define SPINMASK 0
#define CWAIT(bit, a, ph) do { if (SPINMASK & (bit)) mbar_spin(a, ph); else mbar_wait(a, ph); } while (0)
#define NATT_ 3
constexpr int NATT = NATT_;
constexpr int MSGM = 256, MSGT = 512;
constexpr int MIMG = 7168;
constexpr int XST = 28672;

constexpr uint32_t R_AQ = 0, R_AO = 32768, R_RK = 65536, R_RV = 131072;
constexpr uint32_t R_X1 = 0, R_X2 = 28672, R_M = 57344, R_RS = 57344 + NATT * MIMG, R_SC = R_RS + 4096, R_ST = R_SC + 1024, R_TK = R_ST + 4096,
                   R_SV = R_TK + 2048;
constexpr uint32_t R_X0 = 196608, R_BAR = 225280, R_VS = R_BAR + 448;
constexpr uint32_t R_SMEM = R_BAR + 512 + 1024;
enum { B_X = 0, B_RS = 3, B_EXP = 5, B_AQ = 7, B_AO = 8, B_KF = 9, B_KE = 11, B_VF = 13, B_VE = 15, B_PRO = 17, B_GO = 18, B_ST = 19, B_TK = 20, B_KP = 21, B_K1 = 22, B_M = 23, B_N = B_M + NATT };

__device__ __align__(1024) uint8_t g_scm[(size_t)NSEG * NH * NSL * MSGM];
__device__ __align__(1024) uint8_t g_sct[(size_t)NSEG * NH * NSL * MSGT];
__device__ __align__(1024) uint8_t g_mimg[(size_t)NSEG * MIMG];
constexpr int REC = 5120;
__device__ __align__(1024) uint8_t g_kq[(size_t)NSEG * NSL * NH * REC];
__device__ __align__(1024) uint8_t g_vo[(size_t)NSEG * NSL * NH * REC];
enum { CNT_EXP = 0, CNT_QKV = 64, CNT_O = 80, CNT_A = 96, CNT_P = 112, CNT_G = 176, CNT_AD = 177, CNT_W = 180, CNT_N = 188 };
__device__ uint32_t g_cnt[CNT_N];
__device__ uint32_t g_gbar;
#define R_TAIL() do { __syncwarp(); cluster_sync_all(); } while (0)
#define RTR(s, ev) do {} while (0)
#define RTF(s, ...) do {} while (0)

struct RParams {
    CUtensorMap wq, wk, wv, wo, x;
    const bf16* mem0;
    int att_delay, att_gap, tok_delay, sc_delay;
};

template <int TA>
__device__ __forceinline__ void build_tile(uint32_t (&a)[28][4], uint32_t sb, uint32_t aoff, uint32_t ring, int bfull, int bempty, int ba, float scale, int lane) {
    const uint32_t bar = sb + R_BAR;
    const uint32_t lo = desc_lo(sb);
    mbar_wait(bar + ba * 8, 0);
#pragma unroll
    for (int c = 0; c < 7; c++) {
        const int st = c & 1;
        mbar_wait(bar + (bfull + st) * 8, (c >> 1) & 1);
        float d[32];
        wg_fence();
#pragma unroll
        for (int k = 0; k < 16; k++) {
            const uint32_t aa = TA ? aoff + k * 2048 : aoff + (k >> 2) * 8192 + (k & 3) * 32;
            const uint32_t bb = ring + st * 32768 + (k >> 2) * 8192 + (k & 3) * 32;
            wgmma_ss_n64<TA>(d, desc_at(lo, aa), desc_at(lo, bb), k > 0);
        }
        wg_commit();
        wg_wait<0>();
        if (lane == 0) mbar_arrive(bar + (bempty + st) * 8);
#pragma unroll
        for (int j = 0; j < 4; j++) {
            a[4 * c + j][0] = pack_bf16(d[8 * j + 0] * scale, d[8 * j + 1] * scale);
            a[4 * c + j][1] = pack_bf16(d[8 * j + 2] * scale, d[8 * j + 3] * scale);
            a[4 * c + j][2] = pack_bf16(d[8 * j + 4] * scale, d[8 * j + 5] * scale);
            a[4 * c + j][3] = pack_bf16(d[8 * j + 6] * scale, d[8 * j + 7] * scale);
        }
    }
}

__device__ __forceinline__ void token_pass(float (&d)[16], const uint32_t (&a)[28][4], uint32_t xs) {
    const uint32_t lo = desc_lo(xs);
    wg_fence();
#pragma unroll
    for (int k = 0; k < 28; k++) wgmma_rs_n32(d, a[k], desc_at(lo, (k >> 2) * 4096 + (k & 3) * 32), k > 0);
    wg_commit();
    wg_wait<0>();
}

__device__ __forceinline__ uint32_t x_stage(uint32_t sb, int seg) {
    const int st = seg % 3;
    return sb + (st == 0 ? R_X0 : (st == 1 ? R_X1 : R_X2));
}

__device__ __forceinline__ int gather_mem_scores(const uint8_t* m, uint8_t* dst, uint32_t done_bar, int lane) {
    uint4 u0, u1, u2, u3 = make_uint4(0, 0, 0, 0);
    int c = 0;
    while (true) {
        u0 = ld_relaxed_v4(m); u1 = ld_relaxed_v4(m + 512); u2 = ld_relaxed_v4(m + 1024);
        if (lane < 16) u3 = ld_relaxed_v4(m + 1536);
        const uint32_t umx = max(max(max(max(u0.x, u0.y), max(u0.z, u0.w)), max(max(u1.x, u1.y), max(u1.z, u1.w))),
                                 max(max(max(u2.x, u2.y), max(u2.z, u2.w)), max(max(u3.x, u3.y), max(u3.z, u3.w))));
        if (__all_sync(0xffffffffu, umx != SENT)) break;
        if (++c > SPIN_LIMIT) { die(); break; }
    }
    float v0 = (__uint_as_float(u0.x) + __uint_as_float(u1.x)) + (__uint_as_float(u2.x) + __uint_as_float(u3.x));
    float v1 = (__uint_as_float(u0.y) + __uint_as_float(u1.y)) + (__uint_as_float(u2.y) + __uint_as_float(u3.y));
    float v2 = (__uint_as_float(u0.z) + __uint_as_float(u1.z)) + (__uint_as_float(u2.z) + __uint_as_float(u3.z));
    float v3 = (__uint_as_float(u0.w) + __uint_as_float(u1.w)) + (__uint_as_float(u2.w) + __uint_as_float(u3.w));
    v0 += __shfl_xor_sync(0xffffffffu, v0, 16); v1 += __shfl_xor_sync(0xffffffffu, v1, 16);
    v2 += __shfl_xor_sync(0xffffffffu, v2, 16); v3 += __shfl_xor_sync(0xffffffffu, v3, 16);
    float mx = fmaxf(fmaxf(v0, v1), fmaxf(v2, v3));
    if (lane < 16) *reinterpret_cast<float4*>(dst + lane * 16) = make_float4(v0, v1, v2, v3);
    mx = fmaxf(mx, __shfl_xor_sync(0xffffffffu, mx, 1));
    if (lane < 16 && !(lane & 1)) *reinterpret_cast<float*>(dst + 256 + (lane >> 1) * 4) = mx;
    __syncwarp();
    mbar_arrive_if(done_bar, lane == 0);
    return c;
}

__global__ void __launch_bounds__(384, 1) r_kernel(const __grid_constant__ RParams p) {
    extern __shared__ uint8_t smem_raw[];
    const uint32_t sb = (smem_u32(smem_raw) + 1023) & ~1023u;
    uint8_t* sp = smem_raw + (sb - smem_u32(smem_raw));
    const uint32_t bar = sb + R_BAR;
    uint32_t rank; asm("mov.u32 %0, %%cluster_ctarank;" : "=r"(rank));
    const int g = blockIdx.x / R_CS, h = rank;
    const int tid = threadIdx.x, wg = tid >> 7, warp = (tid >> 5) & 3, lane = tid & 31;
    const int gg = lane >> 2, q = lane & 3;

    if (tid == 0 && blockIdx.x == 0) TS(0);
    if (tid == 0) {
        for (int i = 0; i < 3; i++) mbar_init(bar + (B_X + i) * 8, 1);
        for (int i = 0; i < NATT; i++) mbar_init(bar + (B_M + i) * 8, 1);
        for (int i = 0; i < 2; i++) {
            mbar_init(bar + (B_RS + i) * 8, 1); mbar_init(bar + (B_EXP + i) * 8, 8);
            mbar_init(bar + (B_KF + i) * 8, 1); mbar_init(bar + (B_KE + i) * 8, 4);
            mbar_init(bar + (B_VF + i) * 8, 1); mbar_init(bar + (B_VE + i) * 8, 4);
        }
        mbar_init(bar + B_AQ * 8, 1); mbar_init(bar + B_AO * 8, 1);
        mbar_init(bar + B_PRO * 8, 8); mbar_init(bar + B_GO * 8, 1);
        mbar_init(bar + B_ST * 8, 4); mbar_init(bar + B_TK * 8, 2); mbar_init(bar + B_KP * 8, 1); mbar_init(bar + B_K1 * 8, 1);
        asm volatile("fence.mbarrier_init.release.cluster;" ::: "memory");
        for (int i = 0; i < 3; i++) mbar_expect(bar + (B_X + i) * 8, XST);
        for (int i = 0; i < NATT; i++) mbar_expect(bar + (B_M + i) * 8, MIMG);
        for (int i = 0; i < 2; i++) mbar_expect(bar + (B_RS + i) * 8, 2048);
    }
    if (blockIdx.x == 0 && tid >= 64 && tid < 64 + CNT_N) g_cnt[tid - 64] = 0;
    __syncthreads();
    if (tid == 0) {
        if (blockIdx.x == 0) __threadfence();
        asm volatile("griddepcontrol.launch_dependents;" ::: "memory");
    }
    cluster_sync_all();

    if (wg == 0) {
        reg_inc<200>();
        uint32_t a[28][4];
        if (tid == 0 && blockIdx.x == 0) TS(10);
        build_tile<0>(a, sb, R_AQ, R_RK, B_KF, B_KE, B_AQ, 0.0625f * 1.4426950408889634f, lane);
        if (tid == 0) TSMAX(11);
        if (lane == 0) mbar_arrive(bar + B_PRO * 8);
        uint32_t kx[8];
        const uint32_t lrow = lane & 7, lmat = lane >> 3;
        const uint32_t off0 = lrow * 128 + ((lmat ^ lrow) << 4), off1 = lrow * 128 + (((4 + lmat) ^ lrow) << 4);
        const uint32_t offA = g * 1024 + lrow * 128 + (((2 * warp + (lmat & 1)) ^ lrow) << 4);
        constexpr size_t RSEG = (size_t)NSL * NH * REC;
        uint8_t* kqx = g_kq + ((size_t)g * NH + h) * REC + warp * 1024 + lane * 16;
        uint8_t* kqm = g_kq + ((size_t)g * NH + h) * REC + 4096 + warp * 256 + lane * 8;
        uint8_t* msg = g_scm + ((size_t)h * NSL + g) * MSGM + lane * 8;
        float2* scs = reinterpret_cast<float2*>(sp + R_SC);
        const uint32_t sta = sb + R_ST + (warp * 32 + lane) * 16;
        {
            float d[16];
            mbar_wait(bar + B_X * 8, 0);
            if (tid == 0) mbar_expect(bar + B_X * 8, XST);
            token_pass(d, a, x_stage(sb, 0));
#pragma unroll
            for (int n = 0; n < 4; n++) {
                kx[2 * n] = movmatrix_t(pack_bf16(d[4 * n], d[4 * n + 1]));
                kx[2 * n + 1] = movmatrix_t(pack_bf16(d[4 * n + 2], d[4 * n + 3]));
            }
            *reinterpret_cast<uint4*>(kqx) = make_uint4(kx[0], kx[1], kx[2], kx[3]);
            *reinterpret_cast<uint4*>(kqx + 512) = make_uint4(kx[4], kx[5], kx[6], kx[7]);
        }
        if (tid == 0 && blockIdx.x == 0) TS(13);
        for (int s = 0; s < NSEG; s++) {
            const uint32_t par = s & 1;
            float dk[4];
            uint32_t am0, am1, slot;
            bool tok_sent = false;
            for (int att = 0;; att++) {
                if (att < NATT) {
                    CWAIT(1, bar + (B_M + att) * 8, par);
                    slot = sb + R_M + att * MIMG;
                } else {
                    slot = sb + R_M + (NATT - 1) * MIMG;
                    bar_sync(1, 128);
                    const uint4* im = reinterpret_cast<const uint4*>(g_mimg + (size_t)s * MIMG);
                    {
                        uint4 v0, v1, v2, v3 = make_uint4(0, 0, 0, 0);
                        int c = 0;
                        while (true) {
                            v0 = ld_relaxed_v4(im + tid); v1 = ld_relaxed_v4(im + tid + 128); v2 = ld_relaxed_v4(im + tid + 256);
                            if (tid < 64) v3 = ld_relaxed_v4(im + tid + 384);
                            const uint32_t mx = max(max(max(max(v0.x, v0.y), max(v0.z, v0.w)), max(max(v1.x, v1.y), max(v1.z, v1.w))),
                                                    max(max(max(v2.x, v2.y), max(v2.z, v2.w)), max(max(v3.x, v3.y), max(v3.z, v3.w))));
                            if (__all_sync(0xffffffffu, mx != SENT)) break;
                            if (++c > SPIN_LIMIT) { die(); break; }
                        }
                        uint4* sl = reinterpret_cast<uint4*>(sp + (slot - sb));
                        sl[tid] = v0; sl[tid + 128] = v1; sl[tid + 256] = v2;
                        if (tid < 64) sl[tid + 384] = v3;
                    }
                    fence_proxy_async();
                    bar_sync(1, 128);
                }
                RTR(s, 0);
                ldsm_x2(am0, am1, slot + offA);
                uint32_t b[14][4];
#pragma unroll
                for (int j = 0; j < 7; j++) ldsm_x4(b[j][0], b[j][1], b[j][2], b[j][3], slot + (j >> 1) * 1024 + ((j & 1) ? off1 : off0));
                float st[4][4];
#pragma unroll
                for (int n = 0; n < 4; n++) {
                    st[n][0] = st[n][1] = st[n][2] = st[n][3] = 0.f;
                    mma16816v(st[n], am0, 0u, am1, 0u, kx[2 * n], kx[2 * n + 1]);
                }
                const bool a_ok = __all_sync(0xffffffffu, max(am0, am1) != SENT);
                const bool tok_now = a_ok & !tok_sent;
                float dd[4][4];
#pragma unroll
                for (int i = 0; i < 4; i++) dd[i][0] = dd[i][1] = dd[i][2] = dd[i][3] = 0.f;
                uint32_t mx = 0;
#pragma unroll
                for (int j = 0; j < 14; j++) {
                    if (j == 2) {
                        asm volatile("st.shared.v4.f32 [%0], {%1,%2,%3,%4};" :: "r"(sta), "f"(st[0][0]), "f"(st[0][1]), "f"(st[1][0]), "f"(st[1][1]) : "memory");
                        asm volatile("st.shared.v4.f32 [%0], {%1,%2,%3,%4};" :: "r"(sta + 2048), "f"(st[2][0]), "f"(st[2][1]), "f"(st[3][0]), "f"(st[3][1]) : "memory");
                        __syncwarp();
                        mbar_arrive_if(bar + B_ST * 8, tok_now & (lane == 0) & (s < NSEG - 1));
                        tok_sent = tok_sent | tok_now;
                    }
                    mma16816v(dd[(2 * j) & 3], a[2 * j][0], a[2 * j][1], a[2 * j][2], a[2 * j][3], b[j][0], b[j][1]);
                    mma16816v(dd[(2 * j + 1) & 3], a[2 * j + 1][0], a[2 * j + 1][1], a[2 * j + 1][2], a[2 * j + 1][3], b[j][2], b[j][3]);
                    mx = max(max(mx, b[j][0]), max(b[j][1], max(b[j][2], b[j][3])));
                    if (j + 7 < 14) ldsm_x4(b[j + 7][0], b[j + 7][1], b[j + 7][2], b[j + 7][3], slot + ((j + 7) >> 1) * 1024 + (((j + 7) & 1) ? off1 : off0));
                }
#pragma unroll
                for (int i = 0; i < 4; i++) dk[i] = (dd[0][i] + dd[1][i]) + (dd[2][i] + dd[3][i]);
                if (__all_sync(0xffffffffu, mx != SENT)) break;
            }
            RTR(s, 12);
            const uint32_t km0 = movmatrix_t(pack_bf16(dk[0], dk[1])), km1 = movmatrix_t(pack_bf16(dk[2], dk[3]));
            if (tid == 0) *reinterpret_cast<volatile uint32_t*>(sp + R_VS) = slot;
            if (s < NSEG - 1) {
                float sm[4] = {0, 0, 0, 0};
                mma16816(sm, am0, 0u, am1, 0u, km0, km1);
                bar_arrive(3, 256);
                if (warp != 0) scs[warp * 32 + lane] = make_float2(sm[0], sm[1]);
                RTR(s, 13);
                bar_sync(1, 128);
                if (warp == 0) {
                    const float2 x1 = scs[32 + lane], x2 = scs[64 + lane], x3 = scs[96 + lane];
                    const uint32_t w0 = __float_as_uint((sm[0] + x1.x) + (x2.x + x3.x)), w1 = __float_as_uint((sm[1] + x1.y) + (x2.y + x3.y));
                    st_relaxed_v2(msg + (size_t)s * (NH * NSL * MSGM), w0, w1);
                    mbar_arrive_if(bar + B_K1 * 8, lane == 0);
                    RTR(s, 1);
                }
            } else {
                bar_arrive(3, 256);
            }
            *reinterpret_cast<uint2*>(kqm + (size_t)s * RSEG) = make_uint2(km0, km1);
            __syncwarp();
            if (lane == 0) mbar_arrive(bar + (B_EXP + (s & 1)) * 8);
            if (tid == 0) {
                for (int i = 0; i < NATT; i++) { mbar_wait(bar + (B_M + i) * 8, par); if (s < NSEG - 1) mbar_expect(bar + (B_M + i) * 8, MIMG); }
            }
            __syncwarp();
            if (s < NSEG - 1) {
                const int seg = s + 1;
                float d[16];
                mbar_wait(bar + (B_X + seg % 3) * 8, (seg / 3) & 1);
                if (tid == 0 && seg + 3 < NSEG) mbar_expect(bar + (B_X + seg % 3) * 8, XST);
                token_pass(d, a, x_stage(sb, seg));
                bar_sync(5, 288);
#pragma unroll
                for (int n = 0; n < 4; n++) {
                    kx[2 * n] = movmatrix_t(pack_bf16(d[4 * n], d[4 * n + 1]));
                    kx[2 * n + 1] = movmatrix_t(pack_bf16(d[4 * n + 2], d[4 * n + 3]));
                }
                uint8_t* o = kqx + (size_t)seg * RSEG;
                *reinterpret_cast<uint4*>(o) = make_uint4(kx[0], kx[1], kx[2], kx[3]);
                *reinterpret_cast<uint4*>(o + 512) = make_uint4(kx[4], kx[5], kx[6], kx[7]);
                RTR(s, 2);
                if (warp == 0) RTF(s, 0, 1, 2, 12, 13);
            }
        }
        if (tid == 0) TSMAX(2);
        R_TAIL();
    } else if (wg == 1) {
        reg_inc<200>();
        uint32_t a[28][4];
        build_tile<1>(a, sb, R_AO, R_RV, B_VF, B_VE, B_AO, 1.0f, lane);
        if (lane == 0) mbar_arrive(bar + B_PRO * 8);
        uint32_t vx[8];
        constexpr size_t RSEG = (size_t)NSL * NH * REC;
        uint8_t* vox = g_vo + ((size_t)g * NH + h) * REC + warp * 1024 + lane * 16;
        uint8_t* vom = g_vo + ((size_t)g * NH + h) * REC + 4096 + warp * 256 + lane * 8;
        const uint32_t dst = 4 * warp + q;
        const uint32_t rem_rs = mapa(sb + R_RS + h * 128 + gg * 16, dst), rem_bar = mapa(bar + B_RS * 8, dst);
        const float4* tk4 = reinterpret_cast<const float4*>(sp + R_TK);
        {
            float d[16];
            mbar_wait(bar + B_X * 8, 0);
            token_pass(d, a, x_stage(sb, 0));
#pragma unroll
            for (int n = 0; n < 4; n++) { vx[2 * n] = pack_bf16(d[4 * n], d[4 * n + 1]); vx[2 * n + 1] = pack_bf16(d[4 * n + 2], d[4 * n + 3]); }
            *reinterpret_cast<uint4*>(vox) = make_uint4(vx[0], vx[1], vx[2], vx[3]);
            *reinterpret_cast<uint4*>(vox + 512) = make_uint4(vx[4], vx[5], vx[6], vx[7]);
        }
        for (int s = 0; s < NSEG; s++) {
            bar_sync(3, 256);
            const uint32_t slot = *reinterpret_cast<volatile uint32_t*>(sp + R_VS);
            float dm[4];
            const uint32_t mlo = desc_lo(slot);
            wg_fence();
#pragma unroll
            for (int k = 0; k < 28; k++) wgmma_rs_n8(dm, a[k], desc_at(mlo, (k >> 2) * 1024 + (k & 3) * 32), k > 0);
            wg_commit();
            wg_wait<0>();
            const uint32_t vm0 = pack_bf16(dm[0], dm[1]), vm1 = pack_bf16(dm[2], dm[3]);
            if (s < NSEG - 1) {
                RTR(s, 3);
                CWAIT(2, bar + B_TK * 8, s & 1);
                float4 ta = tk4[lane], tb = tk4[32 + lane];
                { const float4 tc = tk4[64 + lane], td = tk4[96 + lane];
                  ta.x += tc.x; ta.y += tc.y; ta.z += tc.z; ta.w += tc.w; tb.x += td.x; tb.y += td.y; tb.z += td.z; tb.w += td.w; }
                float tmax = fmaxf(fmaxf(fmaxf(ta.x, ta.y), fmaxf(ta.z, ta.w)), fmaxf(fmaxf(tb.x, tb.y), fmaxf(tb.z, tb.w)));
                tmax = fmaxf(tmax, __shfl_xor_sync(0xffffffffu, tmax, 1));
                tmax = fmaxf(tmax, __shfl_xor_sync(0xffffffffu, tmax, 2));
                ta.x = ex2(ta.x - tmax); ta.y = ex2(ta.y - tmax); ta.z = ex2(ta.z - tmax); ta.w = ex2(ta.w - tmax);
                tb.x = ex2(tb.x - tmax); tb.y = ex2(tb.y - tmax); tb.z = ex2(tb.z - tmax); tb.w = ex2(tb.w - tmax);
                CWAIT(2, bar + B_KP * 8, s & 1);
                const float2 sv = *reinterpret_cast<const float2*>(sp + R_SV + lane * 8);
                const float mxv = fmaxf(*reinterpret_cast<const float*>(sp + R_SV + 256 + gg * 4), tmax);
                RTR(s, 19);
                const float f = ex2(tmax - mxv);
                const uint32_t em = pack_bf16(ex2(sv.x - mxv), ex2(sv.y - mxv));
                const uint32_t e0 = pack_bf16(ta.x * f, ta.y * f), e1 = pack_bf16(ta.z * f, ta.w * f);
                const uint32_t e2 = pack_bf16(tb.x * f, tb.y * f), e3 = pack_bf16(tb.z * f, tb.w * f);
                float o[4] = {0, 0, 0, 0}, z[4] = {0, 0, 0, 0}, o2[4] = {0, 0, 0, 0}, z2[4] = {0, 0, 0, 0};
                const uint32_t one = 0x3F803F80u;
                mma16816(o2, vx[2], vx[3], vx[4], vx[5], e1, e2);
                mma16816(z2, one, one, one, one, e1, e2);
                mma16816(o, vx[6], vx[7], 0u, 0u, e3, 0u);
                mma16816(z, one, one, one, one, e3, 0u);
                mma16816(o, vm0, vm1, vx[0], vx[1], em, e0);
                mma16816(z, one, one, one, one, em, e0);
                z[0] += z2[0]; z[1] += z2[1];
                o[0] += o2[0]; o[1] += o2[1]; o[2] += o2[2]; o[3] += o2[3];
                const float r0 = rcp_approx(z[0]), r1 = rcp_approx(z[1]);
                st_async_v4(rem_rs + (s & 1) * 2048, __float_as_uint(o[0] * r0), __float_as_uint(o[1] * r1),
                            __float_as_uint(o[2] * r0), __float_as_uint(o[3] * r1), rem_bar + (s & 1) * 8);
                RTR(s, 5);
                *reinterpret_cast<uint2*>(vom + (size_t)s * RSEG) = make_uint2(vm0, vm1);
                __syncwarp();
                if (lane == 0) mbar_arrive(bar + (B_EXP + (s & 1)) * 8);
                bar_sync(5, 288);
                const int seg = s + 1;
                float d[16];
                mbar_wait(bar + (B_X + seg % 3) * 8, (seg / 3) & 1);
                token_pass(d, a, x_stage(sb, seg));
#pragma unroll
                for (int n = 0; n < 4; n++) { vx[2 * n] = pack_bf16(d[4 * n], d[4 * n + 1]); vx[2 * n + 1] = pack_bf16(d[4 * n + 2], d[4 * n + 3]); }
                uint8_t* op = vox + (size_t)seg * RSEG;
                *reinterpret_cast<uint4*>(op) = make_uint4(vx[0], vx[1], vx[2], vx[3]);
                *reinterpret_cast<uint4*>(op + 512) = make_uint4(vx[4], vx[5], vx[6], vx[7]);
                RTR(s, 6);
                                if (warp == 0) RTF(s, 3, 5, 6, 19);
            } else {
                *reinterpret_cast<uint2*>(vom + (size_t)s * RSEG) = make_uint2(vm0, vm1);
                __syncwarp();
                if (lane == 0) mbar_arrive(bar + (B_EXP + (s & 1)) * 8);
            }
        }
        R_TAIL();
    } else {
        reg_dec<96>();
        if (warp == 0) {
            const int sg = lane >> 3, g8 = lane & 7;
            const int row = 2 * (h & 3) + (sg & 1), cu = 2 * (h >> 2) + (sg >> 1);
            uint8_t* im = g_mimg + g * 1024 + row * 128 + ((cu ^ row) << 4) + (g8 >> 1) * 4;
            const float4* rs = reinterpret_cast<const float4*>(sp + R_RS);
            if (h == 0) {
                mbar_wait(bar + B_GO * 8, 0);
                if (lane == 0) for (int i = 0; i < NATT; i++) bulk_mc(sb + R_M + i * MIMG, g_mimg, MIMG, bar + (B_M + i) * 8, 0xFFFF);
                __syncwarp();
            }
            for (int s = 0; s < NSEG - 1; s++) {
                const int b = s & 1;
                CWAIT(4, bar + (B_RS + b) * 8, (s >> 1) & 1);
                if (lane == 0) mbar_expect(bar + (B_RS + b) * 8, 2048);
                RTR(s, 7);
                const float4* r = rs + b * 128 + sg * 32 + g8;
                const float4 x0 = r[0], x1 = r[8], x2 = r[16], x3 = r[24];
                const float vx = (x0.x + x1.x) + (x2.x + x3.x), vy = (x0.y + x1.y) + (x2.y + x3.y);
                const float vz = (x0.z + x1.z) + (x2.z + x3.z), vw = (x0.w + x1.w) + (x2.w + x3.w);
                float u0 = (sg & 2) ? vz : vx, u1 = (sg & 2) ? vw : vy;
                const float w0 = (sg & 2) ? vx : vz, w1 = (sg & 2) ? vy : vw;
                u0 += __shfl_xor_sync(0xffffffffu, w0, 16);
                u1 += __shfl_xor_sync(0xffffffffu, w1, 16);
                float u = (sg & 1) ? u1 : u0;
                const float w = (sg & 1) ? u0 : u1;
                u += __shfl_xor_sync(0xffffffffu, w, 8);
                const float o = __shfl_xor_sync(0xffffffffu, u, 1);
                if (!(lane & 1)) st_relaxed(im + (size_t)(s + 1) * MIMG, pack_bf16(u, o));
                RTR(s, 8);
                bar_arrive(5, 288);
                RTF(s, 7, 8);
                if (h == 0) {
                    if (lane == 0) {
                        spin_clks(p.att_delay);
                        for (int i = 0; i < NATT; i++) {
                            bulk_mc(sb + R_M + i * MIMG, g_mimg + (size_t)(s + 1) * MIMG, MIMG, bar + (B_M + i) * 8, 0xFFFF);
                            if (i + 1 < NATT) spin_clks(p.att_gap);
                        }
                    }
                    __syncwarp();
                }
            }
        } else if (warp == 1) {
            if (lane == 0) {
                if (h == 8) tma_3d_mc(sb + R_X0, &p.x, 0, 0, 0, bar + B_X * 8, 0xFFFF);
                mbar_expect(bar + B_AQ * 8, 32768);
                for (int k = 0; k < 4; k++) tma_2d(sb + R_AQ + k * 8192, &p.wq, h * DHB + k * 64, g * 64, bar + B_AQ * 8);
                mbar_expect(bar + B_AO * 8, 32768);
                for (int k = 0; k < 4; k++) tma_2d(sb + R_AO + k * 8192, &p.wo, g * 64, h * DHB + k * 64, bar + B_AO * 8);
                for (int c = 0; c < 7; c++) {
                    const int st = c & 1;
                    if (c >= 2) mbar_wait(bar + (B_KE + st) * 8, ((c >> 1) - 1) & 1);
                    mbar_expect(bar + (B_KF + st) * 8, 32768);
                    for (int k = 0; k < 4; k++) tma_2d(sb + R_RK + st * 32768 + k * 8192, &p.wk, h * DHB + k * 64, c * 64, bar + (B_KF + st) * 8);
                    if (c >= 2) mbar_wait(bar + (B_VE + st) * 8, ((c >> 1) - 1) & 1);
                    mbar_expect(bar + (B_VF + st) * 8, 32768);
                    for (int k = 0; k < 4; k++) tma_2d(sb + R_RV + st * 32768 + k * 8192, &p.wv, h * DHB + k * 64, c * 64, bar + (B_VF + st) * 8);
                }
            }
            __syncwarp();
            const uint8_t* msgi = g_scm + (size_t)h * NSL * MSGM + lane * 16;
            for (int s = 0; s < NSEG - 1; s++) {
                CWAIT(8, bar + B_K1 * 8, s & 1);
                RTR(s, 16);
                spin_clks(p.sc_delay);
                RTR(s, 17);
                const int c = gather_mem_scores(msgi + (size_t)s * (NH * NSL * MSGM), sp + R_SV, bar + B_KP * 8, lane);
                (void)c;
                RTR(s, 18);
                RTR(s, 4);
                RTF(s, 4, 15, 16, 17, 18);
            }
        } else {
            const int t2 = tid - 256 - 64;
            const uint4 sv = make_uint4(SENT, SENT, SENT, SENT);
            uint4* sc4 = reinterpret_cast<uint4*>(g_scm) + (size_t)blockIdx.x * 1024;
            for (int i = t2; i < 1024; i += 64) sc4[i] = sv;
            uint4* st4 = reinterpret_cast<uint4*>(g_sct) + (size_t)blockIdx.x * 2048;
            for (int i = t2; i < 2048; i += 64) st4[i] = sv;
            uint4* m4 = reinterpret_cast<uint4*>(g_mimg + MIMG) + (size_t)blockIdx.x * 252;
            for (int i = t2; i < 252; i += 64) m4[i] = sv;
            if (blockIdx.x == 0) {
                for (int u = t2; u < 448; u += 64) {
                    const int i = u / 56, c = u % 56;
                    const uint4 v = *reinterpret_cast<const uint4*>(p.mem0 + i * DM + c * 8);
                    *reinterpret_cast<uint4*>(g_mimg + (c >> 3) * 1024 + i * 128 + (((c & 7) ^ i) << 4)) = v;
                }
            }
            bar_sync(4, 64);
            if (warp == 3 && lane == 0) {
                mbar_wait(bar + B_PRO * 8, 0);
                __threadfence();
                const uint32_t old = atomicAdd(&g_gbar, 1u);
                const uint32_t target = (old / R_CTAS + 1) * R_CTAS;
                int c = 0;
                while ((int32_t)(ld_acquire(&g_gbar) - target) < 0) { if (++c > SPIN_LIMIT) { die(); break; } }
                fence_proxy_async_all();
                if (blockIdx.x == 0) TS(1);
                mbar_arrive(bar + B_GO * 8);
            }
            if (warp == 2 && h == 8 && lane == 0) {
                mbar_wait(bar + B_GO * 8, 0);
                tma_3d_mc(sb + R_X1, &p.x, 0, SEGL, 0, bar + (B_X + 1) * 8, 0xFFFF);
                tma_3d_mc(sb + R_X2, &p.x, 0, 2 * SEGL, 0, bar + (B_X + 2) * 8, 0xFFFF);
            }
            __syncwarp();
            const float4* stp = reinterpret_cast<const float4*>(sp + R_ST) + lane;
            float4* tk4 = reinterpret_cast<float4*>(sp + R_TK);
            uint8_t* mo = g_sct + ((size_t)h * NSL + g) * MSGT + lane * 16;
            const uint8_t* mi = g_sct + ((size_t)h * NSL + (warp == 3 ? 0 : 4)) * MSGT + lane * 16;
            for (int s = 0; s < NSEG; s++) {
                if (s < NSEG - 1) {
                    CWAIT(16, bar + B_ST * 8, s & 1);
                    if (warp == 2 && h == 8 && lane == 0 && s >= 1 && s + 2 < NSEG)
                        tma_3d_mc(x_stage(sb, s + 2), &p.x, 0, (s + 2) * SEGL, 0, bar + (B_X + (s + 2) % 3) * 8, 0xFFFF);
                    __syncwarp();
                    if (warp == 3) {
                        RTR(s, 14);
                        float4 a0 = stp[0], a1 = stp[128];
#pragma unroll
                        for (int w = 1; w < 4; w++) {
                            const float4 y0 = stp[w * 32], y1 = stp[128 + w * 32];
                            a0.x += y0.x; a0.y += y0.y; a0.z += y0.z; a0.w += y0.w; a1.x += y1.x; a1.y += y1.y; a1.z += y1.z; a1.w += y1.w;
                        }
                        st_relaxed_v4(mo + (size_t)s * (NH * NSL * MSGT), pack_bf16(a0.x, a0.y), pack_bf16(a0.z, a0.w), pack_bf16(a1.x, a1.y), pack_bf16(a1.z, a1.w));
                        RTR(s, 10);
                    }
                    spin_clks(warp == 3 ? p.tok_delay : p.tok_delay + 120);
                    const uint8_t* m = mi + (size_t)s * (NH * NSL * MSGT);
                    uint4 t[4];
                    t[3] = make_uint4(0, 0, 0, 0);
                    int c = 0;
                    while (true) {
                        t[0] = ld_relaxed_v4(m); t[1] = ld_relaxed_v4(m + MSGT); t[2] = ld_relaxed_v4(m + 2 * MSGT);
                        if (warp == 3) t[3] = ld_relaxed_v4(m + 3 * MSGT);
                        uint32_t mx = 0;
#pragma unroll
                        for (int i = 0; i < 4; i++) mx = max(mx, max(max(t[i].x, t[i].y), max(t[i].z, t[i].w)));
                        if (__all_sync(0xffffffffu, mx != SENT)) break;
                        if (++c > SPIN_LIMIT) { die(); break; }
                    }
                    float v[8];
                    v[0] = bf_lo(t[0].x); v[1] = bf_hi(t[0].x); v[2] = bf_lo(t[0].y); v[3] = bf_hi(t[0].y);
                    v[4] = bf_lo(t[0].z); v[5] = bf_hi(t[0].z); v[6] = bf_lo(t[0].w); v[7] = bf_hi(t[0].w);
#pragma unroll
                    for (int i = 1; i < 4; i++) {
                        v[0] += bf_lo(t[i].x); v[1] += bf_hi(t[i].x); v[2] += bf_lo(t[i].y); v[3] += bf_hi(t[i].y);
                        v[4] += bf_lo(t[i].z); v[5] += bf_hi(t[i].z); v[6] += bf_lo(t[i].w); v[7] += bf_hi(t[i].w);
                    }
                    tk4[(warp - 2) * 64 + lane] = make_float4(v[0], v[1], v[2], v[3]);
                    tk4[(warp - 2) * 64 + 32 + lane] = make_float4(v[4], v[5], v[6], v[7]);
                    __syncwarp();
                    mbar_arrive_if(bar + B_TK * 8, lane == 0);
                    if (warp == 3) { RTR(s, 11); RTF(s, 10, 11, 14); }
                }
                if (warp == 2) {
                    mbar_wait(bar + (B_EXP + (s & 1)) * 8, (s >> 1) & 1);
                    if (lane == 0) { __threadfence(); atomicAdd(&g_cnt[CNT_EXP + s], 1u); }
                    __syncwarp();
                }
            }
        }
        R_TAIL();
    }
}

constexpr int QKVN = 3 * DM;
constexpr int PIMG = 40960;
__device__ __align__(1024) bf16 g_qkv[(size_t)SEQ * QKVN];
__device__ __align__(1024) bf16 g_o[(size_t)SEQ * DM];
__device__ __align__(1024) bf16 g_a[(size_t)SEQ * DM];
__device__ __align__(1024) uint8_t g_pimg[(size_t)NSEG * PIMG];
__device__ float g_gate[SEQ];

constexpr uint32_t BS_BAR = 229376;
constexpr uint32_t B_SMEM = BS_BAR + 512 + 1024;
enum { BB_F = 0, BB_E = 3, BB_AF = 6, BB_AE = 8, BB_UF = 10, BB_UE = 12, BB_DF = 14, BB_DE = 17, BB_QF = 20, BB_QE = 22, BB_WE = 24, BB_WF = 25, BB_XF = 32, BB_XE = 38, BB_N = 44 };
constexpr uint32_t BS_UQ = 229376 + 384;

struct BParams {
    CUtensorMap x64, wqkv, o128, wo, qkv, xseg;
    const bf16* gate_w;
    const bf16* x;
    bf16* out;
    int np;
};

template <int TB>
__device__ __forceinline__ void wgmma_ss_n224(float (&d)[112], uint64_t a, uint64_t b, int sc) {
    asm volatile("{\n.reg .pred p;\nsetp.ne.b32 p, %114, 0;\n"
                 "wgmma.mma_async.sync.aligned.m64n224k16.f32.bf16.bf16 {"
                 "%0,%1,%2,%3,%4,%5,%6,%7,%8,%9,%10,%11,%12,%13,%14,%15,%16,%17,%18,%19,%20,%21,%22,%23,%24,%25,%26,%27,"
                 "%28,%29,%30,%31,%32,%33,%34,%35,%36,%37,%38,%39,%40,%41,%42,%43,%44,%45,%46,%47,%48,%49,%50,%51,%52,%53,%54,%55,"
                 "%56,%57,%58,%59,%60,%61,%62,%63,%64,%65,%66,%67,%68,%69,%70,%71,%72,%73,%74,%75,%76,%77,%78,%79,%80,%81,%82,%83,"
                 "%84,%85,%86,%87,%88,%89,%90,%91,%92,%93,%94,%95,%96,%97,%98,%99,%100,%101,%102,%103,%104,%105,%106,%107,%108,%109,%110,%111"
                 "}, %112, %113, p, 1, 1, 0, %115;\n}"
                 : "+f"(d[0]), "+f"(d[1]), "+f"(d[2]), "+f"(d[3]), "+f"(d[4]), "+f"(d[5]), "+f"(d[6]), "+f"(d[7]), "+f"(d[8]), "+f"(d[9]),
                   "+f"(d[10]), "+f"(d[11]), "+f"(d[12]), "+f"(d[13]), "+f"(d[14]), "+f"(d[15]), "+f"(d[16]), "+f"(d[17]), "+f"(d[18]), "+f"(d[19]),
                   "+f"(d[20]), "+f"(d[21]), "+f"(d[22]), "+f"(d[23]), "+f"(d[24]), "+f"(d[25]), "+f"(d[26]), "+f"(d[27]), "+f"(d[28]), "+f"(d[29]),
                   "+f"(d[30]), "+f"(d[31]), "+f"(d[32]), "+f"(d[33]), "+f"(d[34]), "+f"(d[35]), "+f"(d[36]), "+f"(d[37]), "+f"(d[38]), "+f"(d[39]),
                   "+f"(d[40]), "+f"(d[41]), "+f"(d[42]), "+f"(d[43]), "+f"(d[44]), "+f"(d[45]), "+f"(d[46]), "+f"(d[47]), "+f"(d[48]), "+f"(d[49]),
                   "+f"(d[50]), "+f"(d[51]), "+f"(d[52]), "+f"(d[53]), "+f"(d[54]), "+f"(d[55]), "+f"(d[56]), "+f"(d[57]), "+f"(d[58]), "+f"(d[59]),
                   "+f"(d[60]), "+f"(d[61]), "+f"(d[62]), "+f"(d[63]), "+f"(d[64]), "+f"(d[65]), "+f"(d[66]), "+f"(d[67]), "+f"(d[68]), "+f"(d[69]),
                   "+f"(d[70]), "+f"(d[71]), "+f"(d[72]), "+f"(d[73]), "+f"(d[74]), "+f"(d[75]), "+f"(d[76]), "+f"(d[77]), "+f"(d[78]), "+f"(d[79]),
                   "+f"(d[80]), "+f"(d[81]), "+f"(d[82]), "+f"(d[83]), "+f"(d[84]), "+f"(d[85]), "+f"(d[86]), "+f"(d[87]), "+f"(d[88]), "+f"(d[89]),
                   "+f"(d[90]), "+f"(d[91]), "+f"(d[92]), "+f"(d[93]), "+f"(d[94]), "+f"(d[95]), "+f"(d[96]), "+f"(d[97]), "+f"(d[98]), "+f"(d[99]),
                   "+f"(d[100]), "+f"(d[101]), "+f"(d[102]), "+f"(d[103]), "+f"(d[104]), "+f"(d[105]), "+f"(d[106]), "+f"(d[107]), "+f"(d[108]), "+f"(d[109]),
                   "+f"(d[110]), "+f"(d[111])
                 : "l"(a), "l"(b), "r"(sc), "n"(TB));
}

__device__ __forceinline__ void wait_count(const uint32_t* cnt, uint32_t target) {
    int c = 0;
    while (ld_acquire(cnt) < target) { __nanosleep(32); if (++c > SPIN_LIMIT) { die(); break; } }
}
__device__ __forceinline__ void signal_count(uint32_t* cnt) {
    __threadfence();
    atomicAdd(cnt, 1u);
}

constexpr uint32_t G_STAGE = 49152, G_CST = 3 * G_STAGE, G_CROW = 464;
__device__ __forceinline__ void gemm_produce(uint32_t sb, const CUtensorMap* ta, const CUtensorMap* tw, int m0, int n0, uint32_t& it) {
    const uint32_t bar = sb + BS_BAR;
    for (int kb = 0; kb < 7; kb++, it++) {
        const uint32_t st = it % 3, rnd = it / 3;
        if (rnd >= 1) mbar_wait(bar + (BB_E + st) * 8, (rnd - 1) & 1);
        mbar_expect(bar + (BB_F + st) * 8, G_STAGE);
        tma_2d(sb + st * G_STAGE, ta, kb * 64, m0, bar + (BB_F + st) * 8);
        for (int j = 0; j < 4; j++) tma_2d(sb + st * G_STAGE + 16384 + j * 8192, tw, n0 + j * 64, kb * 64, bar + (BB_F + st) * 8);
    }
}
__device__ __forceinline__ void gemm_consume(uint32_t sb, uint8_t* sp, bf16* c, int ldc, int m0, int n0, uint32_t& it, int wg, int warp, int lane) {
    const uint32_t bar = sb + BS_BAR;
    float d[112];
    const uint32_t lo = desc_lo(sb);
    uint32_t prev = 0;
#pragma unroll 1
    for (int kb = 0; kb < 7; kb++, it++) {
        const uint32_t st = it % 3;
        mbar_wait(bar + (BB_F + st) * 8, (it / 3) & 1);
        const uint32_t la = lo + ((st * G_STAGE + wg * 8192) >> 4);
        const uint32_t lb = ((lo & 0xFFFFu) + ((st * G_STAGE + 16384) >> 4)) | (512u << 16);
        wg_fence();
#pragma unroll
        for (int k = 0; k < 4; k++) wgmma_ss_n224<1>(d, desc_at(la, k * 32), desc_at(lb, k * 2048), (kb | k) != 0);
        wg_commit();
        if (kb > 0) { wg_wait<1>(); if (lane == 0) mbar_arrive(bar + (BB_E + prev) * 8); }
        prev = st;
    }
    wg_wait<0>();
    if (lane == 0) mbar_arrive(bar + (BB_E + prev) * 8);
    const uint32_t wrow = (wg * 64 + warp * 16);
    const uint32_t sa = sb + G_CST + (wrow + (lane & 7) + ((lane >> 3) & 1) * 8) * G_CROW + (lane >> 4) * 16;
#pragma unroll
    for (int j = 0; j < 14; j++)
        stsm_x4(sa + j * 32, pack_bf16(d[8 * j], d[8 * j + 1]), pack_bf16(d[8 * j + 2], d[8 * j + 3]),
                pack_bf16(d[8 * j + 4], d[8 * j + 5]), pack_bf16(d[8 * j + 6], d[8 * j + 7]));
    __syncwarp();
    const uint8_t* rs = sp + G_CST + wrow * G_CROW;
#pragma unroll
    for (int i = 0; i < 14; i++) {
        const int u = i * 32 + lane, r = u / 28, cu = u % 28;
        const uint4 v = *reinterpret_cast<const uint4*>(rs + r * G_CROW + cu * 16);
        *reinterpret_cast<uint4*>(c + (size_t)(m0 + wrow + r) * ldc + n0 + cu * 8) = v;
    }
    __syncwarp();
}

constexpr uint32_t Q_W = 0, Q_A = 172032, Q_C = Q_A + 3 * 16384;
template <int TB>
__device__ __forceinline__ void wgmma_ss_n192(float (&d)[96], uint64_t a, uint64_t b, int sc) {
    asm volatile("{\n.reg .pred p;\nsetp.ne.b32 p, %98, 0;\n"
                 "wgmma.mma_async.sync.aligned.m64n192k16.f32.bf16.bf16 {"
                 "%0,%1,%2,%3,%4,%5,%6,%7,%8,%9,%10,%11,%12,%13,%14,%15,%16,%17,%18,%19,%20,%21,%22,%23,%24,%25,%26,%27,"
                 "%28,%29,%30,%31,%32,%33,%34,%35,%36,%37,%38,%39,%40,%41,%42,%43,%44,%45,%46,%47,%48,%49,%50,%51,%52,%53,%54,%55,"
                 "%56,%57,%58,%59,%60,%61,%62,%63,%64,%65,%66,%67,%68,%69,%70,%71,%72,%73,%74,%75,%76,%77,%78,%79,%80,%81,%82,%83,"
                 "%84,%85,%86,%87,%88,%89,%90,%91,%92,%93,%94,%95"
                 "}, %96, %97, p, 1, 1, 0, %99;\n}"
                 : "+f"(d[0]), "+f"(d[1]), "+f"(d[2]), "+f"(d[3]), "+f"(d[4]), "+f"(d[5]), "+f"(d[6]), "+f"(d[7]), "+f"(d[8]), "+f"(d[9]),
                   "+f"(d[10]), "+f"(d[11]), "+f"(d[12]), "+f"(d[13]), "+f"(d[14]), "+f"(d[15]), "+f"(d[16]), "+f"(d[17]), "+f"(d[18]), "+f"(d[19]),
                   "+f"(d[20]), "+f"(d[21]), "+f"(d[22]), "+f"(d[23]), "+f"(d[24]), "+f"(d[25]), "+f"(d[26]), "+f"(d[27]), "+f"(d[28]), "+f"(d[29]),
                   "+f"(d[30]), "+f"(d[31]), "+f"(d[32]), "+f"(d[33]), "+f"(d[34]), "+f"(d[35]), "+f"(d[36]), "+f"(d[37]), "+f"(d[38]), "+f"(d[39]),
                   "+f"(d[40]), "+f"(d[41]), "+f"(d[42]), "+f"(d[43]), "+f"(d[44]), "+f"(d[45]), "+f"(d[46]), "+f"(d[47]), "+f"(d[48]), "+f"(d[49]),
                   "+f"(d[50]), "+f"(d[51]), "+f"(d[52]), "+f"(d[53]), "+f"(d[54]), "+f"(d[55]), "+f"(d[56]), "+f"(d[57]), "+f"(d[58]), "+f"(d[59]),
                   "+f"(d[60]), "+f"(d[61]), "+f"(d[62]), "+f"(d[63]), "+f"(d[64]), "+f"(d[65]), "+f"(d[66]), "+f"(d[67]), "+f"(d[68]), "+f"(d[69]),
                   "+f"(d[70]), "+f"(d[71]), "+f"(d[72]), "+f"(d[73]), "+f"(d[74]), "+f"(d[75]), "+f"(d[76]), "+f"(d[77]), "+f"(d[78]), "+f"(d[79]),
                   "+f"(d[80]), "+f"(d[81]), "+f"(d[82]), "+f"(d[83]), "+f"(d[84]), "+f"(d[85]), "+f"(d[86]), "+f"(d[87]), "+f"(d[88]), "+f"(d[89]),
                   "+f"(d[90]), "+f"(d[91]), "+f"(d[92]), "+f"(d[93]), "+f"(d[94]), "+f"(d[95])
                 : "l"(a), "l"(b), "r"(sc), "n"(TB));
}
__device__ __forceinline__ void qkv_range(int cta, int nb, int& u0, int& u1) { u0 = cta * 112 / nb; u1 = (cta + 1) * 112 / nb; }
__device__ __forceinline__ void qkv_produce(uint32_t sb, const CUtensorMap* tx64, const CUtensorMap* tw, int cta, int nb) {
    const uint32_t bar = sb + BS_BAR;
    int u0, u1; qkv_range(cta, nb, u0, u1);
    uint32_t ia = 0, iw = 0;
    int cur_n = -1;
    for (int u = u0; u < u1; u++) {
        const int n = u >> 4, m = u & 15;
        const bool new_w = n != cur_n;
        if (new_w) {
            if (iw > 0) mbar_wait(bar + BB_WE * 8, (iw - 1) & 1);
            cur_n = n; iw++;
        }
        for (int w = 0; w < 2; w++) {
            for (int kb = 0; kb < 7; kb++) {
                if (new_w && w == 0) {
                    mbar_expect(bar + (BB_WF + kb) * 8, 24576);
                    for (int jj = 0; jj < 3; jj++) tma_2d(sb + Q_W + (kb * 3 + jj) * 8192, tw, n * 192 + jj * 64, kb * 64, bar + (BB_WF + kb) * 8);
                }
                const uint32_t i2 = ia + kb, st = i2 % 3;
                if (i2 >= 3) mbar_wait(bar + (BB_XE + w * 3 + st) * 8, ((i2 / 3) - 1) & 1);
                mbar_expect(bar + (BB_XF + w * 3 + st) * 8, 8192);
                tma_2d(sb + Q_A + (w * 3 + st) * 8192, tx64, kb * 64, m * 128 + w * 64, bar + (BB_XF + w * 3 + st) * 8);
            }
        }
        ia += 7;
    }
}
__device__ __forceinline__ void qkv_consume(uint32_t sb, uint8_t* sp, int cta, int nb, int& nsig, int wg, int warp, int lane) {
    const uint32_t bar = sb + BS_BAR;
    int u0, u1; qkv_range(cta, nb, u0, u1);
    const uint32_t lo = desc_lo(sb);
    uint32_t ia = 0, iw = 0;
    int cur_n = -1;
#pragma unroll 1
    for (int u = u0; u < u1; u++) {
        const int n = u >> 4, m = u & 15;
        const bool new_w = n != cur_n;
        if (new_w) { cur_n = n; iw++; }
        float d[96];
        uint32_t prev = 0;
        if (wg == 1) bar_sync(9, 256); else if (u > u0) bar_sync(8, 256);
#pragma unroll 1
        for (int kb = 0; kb < 7; kb++, ia++) {
            const uint32_t st = ia % 3;
            if (new_w) mbar_wait(bar + (BB_WF + kb) * 8, (iw - 1) & 1);
            mbar_wait(bar + (BB_XF + wg * 3 + st) * 8, (ia / 3) & 1);
            const uint32_t la = lo + ((Q_A + (wg * 3 + st) * 8192) >> 4);
            const uint32_t lb = ((lo & 0xFFFFu) + ((Q_W + kb * 24576) >> 4)) | (512u << 16);
            wg_fence();
#pragma unroll
            for (int k = 0; k < 4; k++) wgmma_ss_n192<1>(d, desc_at(la, k * 32), desc_at(lb, k * 2048), (kb | k) != 0);
            wg_commit();
            if (kb > 0) { wg_wait<1>(); mbar_arrive_if(bar + (BB_XE + wg * 3 + prev) * 8, lane == 0); }
            prev = st;
        }
        if (wg == 0) bar_arrive(9, 256); else if (u + 1 < u1) bar_arrive(8, 256);
        wg_wait<0>();
        mbar_arrive_if(bar + (BB_XE + wg * 3 + prev) * 8, lane == 0);
        if (u + 1 == u1 || ((u + 1) >> 4) != n) mbar_arrive_if(bar + BB_WE * 8, lane == 0);
        const uint32_t wst = Q_C + (wg * 4 + warp) * 1024;
        const uint32_t srow = (lane & 7) + ((lane >> 3) & 1) * 8;
        const uint32_t sa0 = sb + wst + srow * 64 + ((((lane >> 4)) ^ ((srow >> 1) & 3)) << 4);
        const uint32_t sa1 = sb + wst + srow * 64 + (((2 + (lane >> 4)) ^ ((srow >> 1) & 3)) << 4);
        bf16* c = g_qkv + (size_t)(m * 128 + wg * 64 + warp * 16) * QKVN + n * 192;
#pragma unroll
        for (int pt = 0; pt < 6; pt++) {
            const int r0 = 16 * pt;
            stsm_x4(sa0, pack_bf16(d[r0], d[r0 + 1]), pack_bf16(d[r0 + 2], d[r0 + 3]), pack_bf16(d[r0 + 4], d[r0 + 5]), pack_bf16(d[r0 + 6], d[r0 + 7]));
            stsm_x4(sa1, pack_bf16(d[r0 + 8], d[r0 + 9]), pack_bf16(d[r0 + 10], d[r0 + 11]), pack_bf16(d[r0 + 12], d[r0 + 13]), pack_bf16(d[r0 + 14], d[r0 + 15]));
            __syncwarp();
#pragma unroll
            for (int i = 0; i < 2; i++) {
                const int v = i * 32 + lane, r = v >> 2, cu = v & 3;
                const uint4 x = *reinterpret_cast<const uint4*>(sp + wst + r * 64 + ((cu ^ ((r >> 1) & 3)) << 4));
                *reinterpret_cast<uint4*>(c + (size_t)r * QKVN + pt * 32 + cu * 8) = x;
            }
            __syncwarp();
        }
        bar_arrive(3 + (nsig & 1), 288);
        nsig++;
    }
}

constexpr uint32_t A_STAGE = 114688;
struct AttnState { float o[2][4][4], l[2][4], mrow[2][2]; };

__device__ __forceinline__ void attn_scores(float (&s)[2][6][4], const uint32_t (&qa)[2][2][4], uint32_t kaddr) {
#pragma unroll
    for (int j = 0; j < 6; j++) {
        uint32_t b0, b1, b2, b3;
        ldsm_x4(b0, b1, b2, b3, kaddr + j * 1024);
#pragma unroll
        for (int mt = 0; mt < 2; mt++) {
            s[mt][j][0] = s[mt][j][1] = s[mt][j][2] = s[mt][j][3] = 0.f;
            mma16816(s[mt][j], qa[mt][0][0], qa[mt][0][1], qa[mt][0][2], qa[mt][0][3], b0, b1);
            mma16816(s[mt][j], qa[mt][1][0], qa[mt][1][1], qa[mt][1][2], qa[mt][1][3], b2, b3);
        }
    }
}
template <int MASK>
__device__ __forceinline__ void attn_mask(float (&s)[2][6][4], int t0) {
    if (MASK == 1) {
#pragma unroll
        for (int mt = 0; mt < 2; mt++)
#pragma unroll
            for (int j = 0; j < 4; j++)
#pragma unroll
                for (int e = 0; e < 4; e++)
                    if (t0 <= 16 * mt + 8 * (e >> 1) - 8 * j - (e & 1)) s[mt][j][e] = -INFINITY;
    }
    if (MASK == 2) {
#pragma unroll
        for (int mt = 0; mt < 2; mt++)
#pragma unroll
            for (int j = 2; j < 6; j++)
#pragma unroll
                for (int e = 0; e < 4; e++)
                    if (t0 > 16 + 16 * mt + 8 * (e >> 1) - 8 * j - (e & 1)) s[mt][j][e] = -INFINITY;
    }
}
__device__ __forceinline__ void attn_update(AttnState& a, const float (&s)[2][6][4], uint32_t vb0, uint32_t vb1) {
    const float cs = 0.18898223650461361f * 1.4426950408889634f;
    const uint32_t one = 0x3F803F80u;
    uint32_t pa[2][3][4];
#pragma unroll
    for (int mt = 0; mt < 2; mt++)
#pragma unroll
        for (int hf = 0; hf < 2; hf++) {
            float mx = fmaxf(fmaxf(fmaxf(s[mt][0][2 * hf], s[mt][0][2 * hf + 1]), fmaxf(s[mt][1][2 * hf], s[mt][1][2 * hf + 1])),
                             fmaxf(fmaxf(s[mt][2][2 * hf], s[mt][2][2 * hf + 1]), fmaxf(s[mt][3][2 * hf], s[mt][3][2 * hf + 1])));
            mx = fmaxf(mx, fmaxf(fmaxf(s[mt][4][2 * hf], s[mt][4][2 * hf + 1]), fmaxf(s[mt][5][2 * hf], s[mt][5][2 * hf + 1])));
            mx = fmaxf(mx, __shfl_xor_sync(0xffffffffu, mx, 1));
            mx = fmaxf(mx, __shfl_xor_sync(0xffffffffu, mx, 2));
            const float mn = fmaxf(a.mrow[mt][hf], mx);
            const float alpha = ex2((a.mrow[mt][hf] - mn) * cs);
            a.mrow[mt][hf] = mn;
            const float mc = mn * cs;
#pragma unroll
            for (int j = 0; j < 6; j++)
                pa[mt][j >> 1][(j & 1) * 2 + hf] = pack_bf16(ex2(fmaf(s[mt][j][2 * hf], cs, -mc)), ex2(fmaf(s[mt][j][2 * hf + 1], cs, -mc)));
            a.l[mt][2 * hf] *= alpha;
#pragma unroll
            for (int n = 0; n < 4; n++) { a.o[mt][n][2 * hf] *= alpha; a.o[mt][n][2 * hf + 1] *= alpha; }
        }
#pragma unroll
    for (int ks = 0; ks < 3; ks++) {
        uint32_t v0, v1, v2, v3, v4, v5, v6, v7;
        ldsm_x4_t(v0, v1, v2, v3, vb0 + ks * 2048);
        ldsm_x4_t(v4, v5, v6, v7, vb1 + ks * 2048);
#pragma unroll
        for (int mt = 0; mt < 2; mt++) {
            mma16816(a.o[mt][0], pa[mt][ks][0], pa[mt][ks][1], pa[mt][ks][2], pa[mt][ks][3], v0, v1);
            mma16816(a.o[mt][1], pa[mt][ks][0], pa[mt][ks][1], pa[mt][ks][2], pa[mt][ks][3], v2, v3);
            mma16816(a.o[mt][2], pa[mt][ks][0], pa[mt][ks][1], pa[mt][ks][2], pa[mt][ks][3], v4, v5);
            mma16816(a.o[mt][3], pa[mt][ks][0], pa[mt][ks][1], pa[mt][ks][2], pa[mt][ks][3], v6, v7);
            mma16816(a.l[mt], pa[mt][ks][0], pa[mt][ks][1], pa[mt][ks][2], pa[mt][ks][3], one, one);
        }
    }
}

__device__ __forceinline__ void attn_consume(uint32_t stg, int qt, int hp, int w8, int lane) {
    const int qb = w8 & 3, hh = w8 >> 2;
    const int gg = lane >> 2, q = lane & 3;
    const uint32_t uo = hh ? 3 : 0;
    const int q0 = qt * 128 + qb * 32;
    const uint32_t r7 = lane & 7;
    uint32_t qa[2][2][4];
#pragma unroll
    for (int mt = 0; mt < 2; mt++)
#pragma unroll
        for (int ks = 0; ks < 2; ks++) {
            const uint32_t row = qb * 32 + mt * 16 + r7 + ((lane >> 3) & 1) * 8;
            ldsm_x4(qa[mt][ks][0], qa[mt][ks][1], qa[mt][ks][2], qa[mt][ks][3], stg + row * 128 + (((uo + 2 * ks + (lane >> 4)) ^ r7) << 4));
        }
#pragma unroll
    for (int mt = 0; mt < 2; mt++) {
        if (hh == 0) { if (q >= 2) { qa[mt][1][2] = 0; qa[mt][1][3] = 0; } }
        else         { if (q < 2)  { qa[mt][0][0] = 0; qa[mt][0][1] = 0; } }
    }
    AttnState a;
#pragma unroll
    for (int mt = 0; mt < 2; mt++) {
        a.mrow[mt][0] = a.mrow[mt][1] = -INFINITY;
        a.l[mt][0] = a.l[mt][1] = a.l[mt][2] = a.l[mt][3] = 0.f;
#pragma unroll
        for (int n = 0; n < 4; n++) a.o[mt][n][0] = a.o[mt][n][1] = a.o[mt][n][2] = a.o[mt][n][3] = 0.f;
    }
    const uint32_t kb = stg + 16384 + (qb * 32 + r7) * 128 + (((uo + (lane >> 3)) ^ r7) << 4);
    const uint32_t vrow = qb * 32 + r7 + ((lane >> 3) & 1) * 8;
    const uint32_t vb0 = stg + 65536 + vrow * 128 + (((uo + (lane >> 4)) ^ r7) << 4);
    const uint32_t vd = (((uo + 2 + (lane >> 4)) ^ r7) << 4) - (((uo + (lane >> 4)) ^ r7) << 4);
    const int t0 = 2 * q - gg;
    constexpr uint32_t CH = 48 * 128;
#define ATTN_MODE 0
    if (ATTN_MODE == 0 && q0 >= 256) {
#pragma unroll 1
        for (int ch = 0; ch < 6; ch++) {
            float s[2][6][4];
            attn_scores(s, qa, kb + ch * CH);
            if (ch == 0) attn_mask<1>(s, t0);
            if (ch == 5) attn_mask<2>(s, t0);
            attn_update(a, s, vb0 + ch * CH, vb0 + ch * CH + vd);
        }
    } else if (q0 >= 256) {
        float s0[2][6][4], s1[2][6][4];
        attn_scores(s0, qa, kb);
        attn_scores(s1, qa, kb + CH);
        attn_mask<1>(s0, t0);
        attn_update(a, s0, vb0, vb0 + vd);
#pragma unroll 1
        for (int i = 0; i < 2; i++) {
            const uint32_t o1 = (2 * i + 1) * CH;
            attn_scores(s0, qa, kb + o1 + CH);
            attn_update(a, s1, vb0 + o1, vb0 + o1 + vd);
            attn_scores(s1, qa, kb + o1 + 2 * CH);
            attn_update(a, s0, vb0 + o1 + CH, vb0 + o1 + CH + vd);
        }
        attn_mask<2>(s1, t0);
        attn_update(a, s1, vb0 + 5 * CH, vb0 + 5 * CH + vd);
    } else {
        const int kmin = 256 - q0;
#pragma unroll 1
        for (int ch = kmin / 48; ch < 6; ch++) {
            float s[2][6][4];
            attn_scores(s, qa, kb + ch * CH);
            if (ch == 0) attn_mask<1>(s, t0);
            if (ch == 5) attn_mask<2>(s, t0);
#pragma unroll
            for (int j = 0; j < 6; j++)
                if (48 * ch + 8 * j < kmin) {
#pragma unroll
                    for (int mt = 0; mt < 2; mt++) s[mt][j][0] = s[mt][j][1] = s[mt][j][2] = s[mt][j][3] = -INFINITY;
                }
            attn_update(a, s, vb0 + ch * CH, vb0 + ch * CH + vd);
        }
    }
#pragma unroll
    for (int mt = 0; mt < 2; mt++)
#pragma unroll
        for (int hf = 0; hf < 2; hf++) {
            const float inv = rcp_approx(a.l[mt][2 * hf]);
            bf16* op = g_o + (size_t)(q0 + mt * 16 + hf * 8 + gg) * DM + hp * 56 + uo * 8 + 2 * q;
#pragma unroll
            for (int n = 0; n < 4; n++) {
                const int col = (int)uo * 8 + 8 * n + 2 * q;
                if (col >= 28 * hh && col < 28 * hh + 28)
                    *reinterpret_cast<uint32_t*>(op + 8 * n) = pack_bf16(a.o[mt][n][2 * hf] * inv, a.o[mt][n][2 * hf + 1] * inv);
            }
        }
}

constexpr uint32_t U_STAGE = 40960, U_DATA = 2 * U_STAGE;
#define NP_CTAS 5
constexpr int OBIG = NSEG - 6;
constexpr int Q0_UNITS = (NSEG - 2) * 2, Q1_UNITS = OBIG * 2 + (NSEG - OBIG) * 4 + 8;
struct Unit { int s, h0, nh, k, np; bool score; };
__device__ __forceinline__ Unit decode_unit(int q, int u) {
    Unit t; t.h0 = 0; t.nh = 8; t.k = 0; t.np = 1;
    if (q == 0) { t.score = true; t.s = u >> 1; t.h0 = (u & 1) * 8; return t; }
    t.score = false;
    if (u < OBIG * 2) { t.s = u >> 1; t.k = (u & 1) * 2; t.np = 2; return t; }
    u -= OBIG * 2;
    if (u >= 4 && u < 8) { t.score = true; t.s = NSEG - 2; t.h0 = (u - 4) * 4; t.nh = 4; return t; }
    if (u >= 12 && u < 16) { t.score = true; t.s = NSEG - 1; t.h0 = (u - 12) * 4; t.nh = 4; return t; }
    const int v = u < 4 ? u : (u < 12 ? u - 4 : u - 8);
    t.s = OBIG + (v >> 2); t.k = v & 3;
    return t;
}
__device__ __forceinline__ uint32_t p_target(int s) { return s < NSEG - 2 ? 2u : 4u; }

__device__ __forceinline__ void pscore_consume(uint32_t sb, const uint8_t* sp, uint32_t stg, uint32_t& id, uint8_t* img, int h0, int nh, int wg, int warp, int lane) {
    const uint32_t bar = sb + BS_BAR;
    if (wg * 4 >= nh) {
        for (int c = 0; c < 7; c++, id++) {
            const uint32_t st = id % 3;
            mbar_wait(bar + (BB_DF + st) * 8, (id / 3) & 1);
            mbar_arrive_if(bar + (BB_DE + st) * 8, lane == 0);
        }
        return;
    }
    const int h = h0 + wg * 4 + warp;
    const int gg = lane >> 2, q = lane & 3;
    float d0[16], d1[16], d2[16];
    const uint32_t lo = desc_lo(stg);
    uint32_t fa[2][4][3][4];
    auto load_slot = [&](uint32_t (&f)[4][3][4]) {
        const uint32_t st = id % 3;
        mbar_wait(bar + (BB_DF + st) * 8, (id / 3) & 1);
        const uint8_t* rec = sp + U_DATA + st * U_STAGE + wg * 20480 + warp * REC;
#pragma unroll
        for (int i = 0; i < 4; i++) {
            const uint4 xa = *reinterpret_cast<const uint4*>(rec + (2 * i) * 512 + lane * 16);
            const uint4 xb = *reinterpret_cast<const uint4*>(rec + (2 * i + 1) * 512 + lane * 16);
            const uint2 m = *reinterpret_cast<const uint2*>(rec + 4096 + i * 256 + lane * 8);
            f[i][0][0] = m.x; f[i][0][1] = xa.x; f[i][0][2] = m.y; f[i][0][3] = xa.y;
            f[i][1][0] = xa.z; f[i][1][1] = xb.x; f[i][1][2] = xa.w; f[i][1][3] = xb.y;
            f[i][2][0] = xb.z; f[i][2][1] = 0u; f[i][2][2] = xb.w; f[i][2][3] = 0u;
        }
        id++;
    };
    load_slot(fa[0]);
#pragma unroll
    for (int c = 0; c < 7; c++) {
        wg_fence();
#pragma unroll
        for (int i = 0; i < 4; i++) {
            const uint64_t db = desc_at(lo, c * 4096 + i * 32);
            wgmma_rs_n32(d0, fa[c & 1][i][0], db, (c | i) != 0);
            wgmma_rs_n32(d1, fa[c & 1][i][1], db, (c | i) != 0);
            wgmma_rs_n32(d2, fa[c & 1][i][2], db, (c | i) != 0);
        }
        wg_commit();
        __syncwarp();
        mbar_arrive_if(bar + (BB_DE + (id - 1) % 3) * 8, lane == 0);
        if (c + 1 < 7) load_slot(fa[(c + 1) & 1]);
        wg_wait<0>();
    }
    float v[8][5], mx[8], sum[8];
#pragma unroll
    for (int c = 0; c < 8; c++) {
        const int n = c >> 1, e = c & 1, t = 8 * n + 2 * q + e;
        v[c][0] = d0[4 * n + e]; v[c][1] = d0[4 * n + 2 + e]; v[c][2] = d1[4 * n + e]; v[c][3] = d1[4 * n + 2 + e]; v[c][4] = d2[4 * n + e];
#pragma unroll
        for (int bb = 0; bb < 4; bb++) if (8 * bb + gg > t) v[c][1 + bb] = -INFINITY;
        mx[c] = fmaxf(fmaxf(fmaxf(v[c][0], v[c][1]), fmaxf(v[c][2], v[c][3])), v[c][4]);
    }
#pragma unroll
    for (int o = 4; o <= 16; o <<= 1)
#pragma unroll
        for (int c = 0; c < 8; c++) mx[c] = fmaxf(mx[c], __shfl_xor_sync(0xffffffffu, mx[c], o));
#pragma unroll
    for (int c = 0; c < 8; c++) {
        sum[c] = 0.f;
#pragma unroll
        for (int bb = 0; bb < 5; bb++) { v[c][bb] = ex2(v[c][bb] - mx[c]); sum[c] += v[c][bb]; }
    }
#pragma unroll
    for (int o = 4; o <= 16; o <<= 1)
#pragma unroll
        for (int c = 0; c < 8; c++) sum[c] += __shfl_xor_sync(0xffffffffu, sum[c], o);
#pragma unroll
    for (int n = 0; n < 4; n++) {
        const float i0 = rcp_approx(sum[2 * n]), i1 = rcp_approx(sum[2 * n + 1]);
        const int t = 8 * n + gg;
        uint8_t* rowt = img + ((h >> 1) & 3) * 4096 + t * 128 + 4 * q;
#pragma unroll
        for (int bb = 0; bb < 4; bb++) {
            const uint32_t w = movmatrix_t(pack_bf16(v[2 * n][1 + bb] * i0, v[2 * n + 1][1 + bb] * i1));
            *reinterpret_cast<uint32_t*>(rowt + ((((h & 1) * 4 + bb) ^ (t & 7)) << 4)) = w;
        }
        const uint32_t w = movmatrix_t(pack_bf16(v[2 * n][0] * i0, v[2 * n + 1][0] * i1));
        *reinterpret_cast<uint32_t*>(img + 16384 + t * 128 + 4 * q + (((h & 7) ^ (t & 7)) << 4)) = w;
    }
}

__device__ __forceinline__ void pv_consume(uint32_t sb, const uint8_t* sp, uint32_t img0, uint32_t img1, uint32_t& id, int s, int g, int wg, int warp, int lane, bf16* out) {
    const uint32_t bar = sb + BS_BAR;
    const int gg = lane >> 2, q = lane & 3;
    float d[16];
    const uint32_t lo0 = desc_lo(img0), lo1 = desc_lo(img1);
    uint32_t aw[4][2]; float gt[4];
    if (g < NSL) {
#pragma unroll
        for (int n = 0; n < 4; n++) {
            const int t = s * SEGL + 8 * n + gg;
            gt[n] = __ldcg(g_gate + t);
#pragma unroll
            for (int hf = 0; hf < 2; hf++)
                aw[n][hf] = __ldcg(reinterpret_cast<const uint32_t*>(g_a + (size_t)t * DM + 64 * g + 16 * warp + 8 * hf + 2 * q));
        }
    }
    if (g >= NSL) {
        for (int c = 0; c < 4; c++, id++) {
            const uint32_t st = id % 3;
            mbar_wait(bar + (BB_DF + st) * 8, (id / 3) & 1);
            mbar_arrive_if(bar + (BB_DE + st) * 8, lane == 0);
        }
        return;
    }
    uint32_t fa[2][4][2][4], fm[2][2][4];
    auto load_slot = [&](uint32_t (&f)[4][2][4], uint32_t (&fmm)[2][4]) {
        const uint32_t st = id % 3;
        mbar_wait(bar + (BB_DF + st) * 8, (id / 3) & 1);
        const uint8_t* base = sp + U_DATA + st * U_STAGE + wg * 20480;
#pragma unroll
        for (int i = 0; i < 4; i++) {
            const uint8_t* rec = base + i * REC;
            const uint4 xa = *reinterpret_cast<const uint4*>(rec + (2 * warp) * 512 + lane * 16);
            const uint4 xb = *reinterpret_cast<const uint4*>(rec + (2 * warp + 1) * 512 + lane * 16);
            const uint2 m = *reinterpret_cast<const uint2*>(rec + 4096 + warp * 256 + lane * 8);
            f[i][0][0] = xa.x; f[i][0][1] = xa.y; f[i][0][2] = xa.z; f[i][0][3] = xa.w;
            f[i][1][0] = xb.x; f[i][1][1] = xb.y; f[i][1][2] = xb.z; f[i][1][3] = xb.w;
            fmm[i >> 1][(i & 1) * 2] = m.x; fmm[i >> 1][(i & 1) * 2 + 1] = m.y;
        }
        id++;
    };
    load_slot(fa[0], fm[0]);
#pragma unroll
    for (int c = 0; c < 4; c++) {
        const uint32_t lo = (c >> 1) ? lo1 : lo0;
        wg_fence();
#pragma unroll
        for (int i = 0; i < 4; i++) {
            wgmma_rs_n32(d, fa[c & 1][i][0], desc_at(lo, (2 * (c & 1) + (i >> 1)) * 4096 + (i & 1) * 64), (c | i) != 0);
            wgmma_rs_n32(d, fa[c & 1][i][1], desc_at(lo, (2 * (c & 1) + (i >> 1)) * 4096 + (i & 1) * 64 + 32), 1);
            if (i & 1) wgmma_rs_n32(d, fm[c & 1][i >> 1], desc_at(lo, 16384 + (c & 1) * 64 + (i >> 1) * 32), 1);
        }
        wg_commit();
        __syncwarp();
        mbar_arrive_if(bar + (BB_DE + (id - 1) % 3) * 8, lane == 0);
        if (c + 1 < 4) load_slot(fa[(c + 1) & 1], fm[(c + 1) & 1]);
        wg_wait<0>();
    }
#pragma unroll
    for (int n = 0; n < 4; n++) {
        const int t = s * SEGL + 8 * n + gg;
#pragma unroll
        for (int hf = 0; hf < 2; hf++) {
            const uint32_t bw = movmatrix_t(pack_bf16(d[4 * n + 2 * hf], d[4 * n + 2 * hf + 1]));
            const size_t off = (size_t)t * DM + 64 * g + 16 * warp + 8 * hf + 2 * q;
            *reinterpret_cast<uint32_t*>(out + off) = pack_bf16(gt[n] * bf_lo(aw[n][hf]) + (1.0f - gt[n]) * bf_lo(bw), gt[n] * bf_hi(aw[n][hf]) + (1.0f - gt[n]) * bf_hi(bw));
        }
    }
}

__device__ __forceinline__ int queue_post(uint32_t sb, uint8_t* sp, uint32_t& iq, uint32_t* counter, int n_units, int stop_at = 1 << 30) {
    const uint32_t bar = sb + BS_BAR, sl = iq & 1;
    int u = -1;
    if (stop_at == (1 << 30) || (int)ld_relaxed(counter) < stop_at) u = (int)atomicAdd(counter, 1u);
    if (u >= n_units) u = -1;
    if (iq >= 2) mbar_wait(bar + (BB_QE + sl) * 8, ((iq >> 1) - 1) & 1);
    *reinterpret_cast<volatile int*>(sp + BS_UQ + sl * 4) = u;
    mbar_arrive(bar + (BB_QF + sl) * 8);
    iq++;
    return u;
}
__device__ __forceinline__ void queue_put(uint32_t sb, uint8_t* sp, uint32_t& iq, int v) {
    const uint32_t bar = sb + BS_BAR, sl = iq & 1;
    if (iq >= 2) mbar_wait(bar + (BB_QE + sl) * 8, ((iq >> 1) - 1) & 1);
    *reinterpret_cast<volatile int*>(sp + BS_UQ + sl * 4) = v;
    mbar_arrive(bar + (BB_QF + sl) * 8);
    iq++;
}
__device__ __forceinline__ int queue_get(uint32_t sb, const uint8_t* sp, uint32_t& iq, int lane) {
    const uint32_t bar = sb + BS_BAR, sl = iq & 1;
    mbar_wait(bar + (BB_QF + sl) * 8, (iq >> 1) & 1);
    const int u = *reinterpret_cast<const volatile int*>(sp + BS_UQ + sl * 4);
    const bool got = __all_sync(0xffffffffu, u >= -1);
    mbar_arrive_if(bar + (BB_QE + sl) * 8, got & (lane == 0));
    iq++;
    return u;
}

__global__ void __launch_bounds__(384, 1) b_kernel(const __grid_constant__ BParams p) {
    extern __shared__ uint8_t smem_raw[];
    const uint32_t sb = (smem_u32(smem_raw) + 1023) & ~1023u;
    uint8_t* sp = smem_raw + (sb - smem_u32(smem_raw));
    const uint32_t bar = sb + BS_BAR;
    const int tid = threadIdx.x, wg = tid >> 7, warp = (tid >> 5) & 3, lane = tid & 31;
    const int nb = gridDim.x, cta = blockIdx.x;
    if (tid == 0 && blockIdx.x == 0) TS(4);
    if (tid == 0) {
        for (int i = 0; i < 3; i++) {
            mbar_init(bar + (BB_F + i) * 8, 1); mbar_init(bar + (BB_E + i) * 8, 8);
            mbar_init(bar + (BB_DF + i) * 8, 1); mbar_init(bar + (BB_DE + i) * 8, 8);
        }
        for (int i = 0; i < 2; i++) {
            mbar_init(bar + (BB_AF + i) * 8, 1); mbar_init(bar + (BB_AE + i) * 8, 8);
            mbar_init(bar + (BB_UF + i) * 8, 1); mbar_init(bar + (BB_UE + i) * 8, 8);
            mbar_init(bar + (BB_QF + i) * 8, 1); mbar_init(bar + (BB_QE + i) * 8, 9);
        }
        mbar_init(bar + BB_WE * 8, 8);
        for (int i = 0; i < 7; i++) mbar_init(bar + (BB_WF + i) * 8, 1);
        for (int i = 0; i < 6; i++) { mbar_init(bar + (BB_XF + i) * 8, 1); mbar_init(bar + (BB_XE + i) * 8, 4); }
        asm volatile("fence.mbarrier_init.release.cluster;" ::: "memory");
    }
    __syncthreads();
    uint32_t* cnt_qkv = g_cnt + CNT_QKV; uint32_t* cnt_o = g_cnt + CNT_O; uint32_t* cnt_p = g_cnt + CNT_P;

    if (wg == 2) {
        reg_dec<40>();
        if (warp == 0) {
            uint32_t it = 0, iq = 0;
            if (lane == 0) qkv_produce(sb, &p.x64, &p.wqkv, cta, nb);
            __syncwarp();
            bar_sync(1, 288);
            const bool p_cta = cta < p.np;
            if (!p_cta) {
            if (lane == 0) {
                uint32_t ia = 0;
                int u;
                while ((u = queue_post(sb, sp, iq, g_cnt + CNT_W + 1, 128)) >= 0) {
                    const int qt = u >> 3, hp = u & 7;
                    const uint32_t st = ia & 1;
                    if (ia >= 2) mbar_wait(bar + (BB_AE + st) * 8, ((ia >> 1) - 1) & 1);
                    for (int i = (qt >= 2 ? qt - 2 : 0); i <= qt; i++) wait_count(cnt_qkv + i, 7);
                    fence_proxy_async_all();
                    const uint32_t stg = sb + st * A_STAGE, fb = bar + (BB_AF + st) * 8;
                    mbar_expect(fb, A_STAGE);
                    tma_2d(stg, &p.qkv, hp * 56, qt * 128, fb);
                    for (int i = 0; i < 3; i++) {
                        tma_2d(stg + 16384 + i * 16384, &p.qkv, DM + hp * 56, (qt - 2 + i) * 128, fb);
                        tma_2d(stg + 65536 + i * 16384, &p.qkv, 2 * DM + hp * 56, (qt - 2 + i) * 128, fb);
                    }
                    ia++;
                    if (ia >= 2) mbar_wait(bar + (BB_AE + (ia & 1)) * 8, ((ia >> 1) - 1) & 1);
                }
            }
            __syncwarp();
            bar_sync(1, 288);
            if (lane == 0) {
                int u;
                while ((u = queue_post(sb, sp, iq, g_cnt + CNT_W + 2, 32)) >= 0) {
                    wait_count(cnt_o + (u >> 1), 8);
                    fence_proxy_async_all();
                    gemm_produce(sb, &p.o128, &p.wo, (u >> 1) * 128, (u & 1) * 224, it);
                }
            }
                __syncwarp();
                bar_sync(1, 288);
            }
            if (lane == 0) {
                uint32_t iu = 0, id = 0;
                bool gate_ok = false;
                int exp_seen = -1;
                uint32_t smid; asm("mov.u32 %0, %%smid;" : "=r"(smid));
                const bool shared_gpc = smid >= 120 && smid < 124;
                uint32_t* q0 = g_cnt + CNT_W + 3;
                uint32_t* q1 = g_cnt + CNT_W + 4;
                bool q0_open = p_cta;
                {
                    while (true) {
                        int q = 1, u = -1;
                        if (q0_open) {
                            u = (int)atomicAdd(q0, 1u);
                            if (u < Q0_UNITS) q = 0; else { q0_open = false; u = -1; }
                        }
                        if (u < 0) {
                            const int n1 = (int)ld_relaxed(q1);
                            if (n1 >= Q1_UNITS || (shared_gpc && n1 >= OBIG * 2 - 4)) { queue_put(sb, sp, iq, -1); break; }
                            const Unit nx = decode_unit(1, n1);
                            if (!nx.score && !shared_gpc && ld_relaxed(cnt_p + nx.s) < p_target(nx.s)) {
                                const int n0 = (int)ld_relaxed(q0);
                                if (n0 < Q0_UNITS && ld_relaxed(g_cnt + CNT_EXP + (n0 >> 1)) >= R_CTAS && (int)atomicCAS(q0, n0, n0 + 1) == n0) { q = 0; u = n0; }
                            }
                            if (u < 0) {
                                u = (int)atomicAdd(q1, 1u);
                                if (u >= Q1_UNITS) { queue_put(sb, sp, iq, -1); break; }
                            }
                        }
                        queue_put(sb, sp, iq, (q << 12) | u);
                        const Unit t = decode_unit(q, u);
                        const int s = t.s;
                        const uint32_t st = iu & 1;
                        if (iu >= 2) mbar_wait(bar + (BB_UE + st) * 8, ((iu >> 1) - 1) & 1);
                        const uint32_t stg = sb + st * U_STAGE, fb = bar + (BB_UF + st) * 8;
                        bool img_pending = false;
                        if (t.score) {
                            mbar_expect(fb, XST);
                            tma_3d(stg, &p.xseg, 0, s * SEGL, 0, fb);
                        } else {
                            if (!gate_ok) {
                                wait_count(g_cnt + CNT_AD, 32);
                                wait_count(g_cnt + CNT_G, 2 * nb);
                                gate_ok = true;
                            }
                            if (ld_acquire(cnt_p + s) >= p_target(s)) {
                                exp_seen = max(exp_seen, s);
                                fence_proxy_async_all();
                                mbar_expect(fb, PIMG);
                                bulk_ld(stg, g_pimg + (size_t)s * PIMG, PIMG, fb);
                            } else {
                                img_pending = true;
                            }
                        }
                        if (s > exp_seen) { wait_count(g_cnt + CNT_EXP + s, R_CTAS); exp_seen = s; fence_proxy_async_all(); }
                        const int nd = t.score ? 7 : 4 * t.np;
                        for (int c = 0; c < nd; c++, id++) {
                            if (img_pending && c == 3) {
                                wait_count(cnt_p + s, p_target(s));
                                fence_proxy_async_all();
                                mbar_expect(fb, PIMG);
                                bulk_ld(stg, g_pimg + (size_t)s * PIMG, PIMG, fb);
                            }
                            const uint32_t ds = id % 3, rnd = id / 3;
                            if (rnd >= 1) mbar_wait(bar + (BB_DE + ds) * 8, (rnd - 1) & 1);
                            const uint32_t dst = sb + U_DATA + ds * U_STAGE, db = bar + (BB_DF + ds) * 8;
                            if (t.score) {
                                mbar_expect(db, t.nh * REC);
                                bulk_ld(dst, g_kq + (((size_t)s * NSL + c) * NH + t.h0) * REC, t.nh * REC, db);
                            } else {
                                const int g0 = 2 * (t.k + (c >> 2)), quad = c & 3;
                                mbar_expect(db, g0 + 1 < NSL ? 40960 : 20480);
                                bulk_ld(dst, g_vo + (((size_t)s * NSL + g0) * NH + 4 * quad) * REC, 20480, db);
                                if (g0 + 1 < NSL) bulk_ld(dst + 20480, g_vo + (((size_t)s * NSL + g0 + 1) * NH + 4 * quad) * REC, 20480, db);
                            }
                        }
                        iu++;
                    }
                }
            }
        } else if (warp >= 2) {
            uint4 gw[2];
            gw[0] = __ldg(reinterpret_cast<const uint4*>(p.gate_w) + lane);
            gw[1] = lane < 24 ? __ldg(reinterpret_cast<const uint4*>(p.gate_w) + 32 + lane) : make_uint4(0, 0, 0, 0);
            for (int t = cta * 2 + (warp - 2); t < SEQ; t += nb * 2) {
                const uint4* xr = reinterpret_cast<const uint4*>(p.x + (size_t)t * DM);
                const uint4 x0 = __ldg(xr + lane), x1 = lane < 24 ? __ldg(xr + 32 + lane) : make_uint4(0, 0, 0, 0);
                float acc = bf_lo(x0.x) * bf_lo(gw[0].x) + bf_hi(x0.x) * bf_hi(gw[0].x) + bf_lo(x0.y) * bf_lo(gw[0].y) + bf_hi(x0.y) * bf_hi(gw[0].y)
                          + bf_lo(x0.z) * bf_lo(gw[0].z) + bf_hi(x0.z) * bf_hi(gw[0].z) + bf_lo(x0.w) * bf_lo(gw[0].w) + bf_hi(x0.w) * bf_hi(gw[0].w)
                          + bf_lo(x1.x) * bf_lo(gw[1].x) + bf_hi(x1.x) * bf_hi(gw[1].x) + bf_lo(x1.y) * bf_lo(gw[1].y) + bf_hi(x1.y) * bf_hi(gw[1].y)
                          + bf_lo(x1.z) * bf_lo(gw[1].z) + bf_hi(x1.z) * bf_hi(gw[1].z) + bf_lo(x1.w) * bf_lo(gw[1].w) + bf_hi(x1.w) * bf_hi(gw[1].w);
#pragma unroll
                for (int o = 16; o > 0; o >>= 1) acc += __shfl_xor_sync(0xffffffffu, acc, o);
                if (lane == 0) g_gate[t] = 1.0f / (1.0f + __expf(-acc));
            }
            __syncwarp();
            if (lane == 0) signal_count(g_cnt + CNT_G);
        } else if (warp == 1) {
            int n = 0, u;
            uint32_t iq = 0;
            { int u0, u1; qkv_range(cta, nb, u0, u1);
              for (u = u0; u < u1; u++) { bar_sync(3 + (n & 1), 288); if (lane == 0) signal_count(cnt_qkv + (u & 15)); __syncwarp(); n++; } }
            if (cta >= p.np) {
                while ((u = queue_get(sb, sp, iq, lane)) >= 0) { bar_sync(3 + (n & 1), 288); if (lane == 0) signal_count(cnt_o + (u >> 3)); __syncwarp(); n++; }
                while ((u = queue_get(sb, sp, iq, lane)) >= 0) { bar_sync(3 + (n & 1), 288); if (lane == 0) signal_count(g_cnt + CNT_AD); __syncwarp(); n++; }
            }
            while ((u = queue_get(sb, sp, iq, lane)) >= 0) {
                const Unit t = decode_unit(u >> 12, u & 4095);
                if (t.score) { bar_sync(3 + (n & 1), 288); if (lane == 0) signal_count(cnt_p + t.s); __syncwarp(); n++; }
            }
        }
    } else {
        reg_inc<232>();
        const int w8 = wg * 4 + warp;
        uint32_t it = 0, iq = 0;
        int n = 0, u;
        qkv_consume(sb, sp, cta, nb, n, wg, warp, lane);
        if (tid == 0) TSMAX(5);
        bar_sync(1, 288);
        const bool p_cta = cta < p.np;
        if (!p_cta) {
            uint32_t ia = 0;
            while ((u = queue_get(sb, sp, iq, lane)) >= 0) {
                const uint32_t st = ia & 1;
                mbar_wait(bar + (BB_AF + st) * 8, (ia >> 1) & 1);
                attn_consume(sb + st * A_STAGE, u >> 3, u & 7, w8, lane);
                __syncwarp();
                mbar_arrive_if(bar + (BB_AE + st) * 8, lane == 0);
                bar_arrive(3 + (n & 1), 288);
                ia++; n++;
            }
            if (tid == 0) TSMAX(6);
            bar_sync(1, 288);
            while ((u = queue_get(sb, sp, iq, lane)) >= 0) {
                gemm_consume(sb, sp, g_a, DM, (u >> 1) * 128, (u & 1) * 224, it, wg, warp, lane);
                bar_arrive(3 + (n & 1), 288);
                n++;
            }
            if (tid == 0) TSMAX(7);
            bar_sync(1, 288);
        }
        {
            uint32_t iu = 0, id = 0;
            {
                while ((u = queue_get(sb, sp, iq, lane)) >= 0) {
                    const Unit t = decode_unit(u >> 12, u & 4095);
                    const uint32_t st = iu & 1, stg = sb + st * U_STAGE;
                    mbar_wait(bar + (BB_UF + st) * 8, (iu >> 1) & 1);
                    if (t.score) {
                        pscore_consume(sb, sp, stg, id, g_pimg + (size_t)t.s * PIMG + (t.h0 >> 3) * 20480, t.h0, t.nh, wg, warp, lane);
                    } else {
#pragma unroll 1
                        for (int j = 0; j < t.np; j++) pv_consume(sb, sp, stg, stg + 20480, id, t.s, (t.k + j) * 2 + wg, wg, warp, lane, p.out);
                    }
                    __syncwarp();
                    mbar_arrive_if(bar + (BB_UE + st) * 8, lane == 0);
                    if (t.score) { bar_arrive(3 + (n & 1), 288); n++; }
                    iu++;
                }
            }
        }
        if (tid == 0) TSMAX(8);

    }
}

__device__ __align__(1024) bf16 g_fw[(size_t)2 * NH * DM * DM];
__device__ float g_fpart[NH * NMEM * DM];
__device__ bf16 g_fmem[NMEM * DM];
__device__ __forceinline__ float bf(bf16 v) { return __bfloat162float(v); }
__device__ __forceinline__ int rec_tok(int side, int c, int t) {
    const int w = c >> 4, n = t >> 3;
    if (side == 0) { const int k = c & 15; return w * 1024 + (n >> 1) * 512 + ((t & 7) * 4 + ((k & 7) >> 1)) * 16 + ((n & 1) * 2 + (k >> 3)) * 4 + (k & 1) * 2; }
    return w * 1024 + (n >> 1) * 512 + ((c & 7) * 4 + ((t & 7) >> 1)) * 16 + ((n & 1) * 2 + ((c >> 3) & 1)) * 4 + (t & 1) * 2;
}
__device__ __forceinline__ int rec_mem(int side, int c, int j) {
    const int w = c >> 4;
    if (side == 0) { const int k = c & 15; return 4096 + w * 256 + (j * 4 + ((k & 7) >> 1)) * 8 + (k >> 3) * 4 + (k & 1) * 2; }
    return 4096 + w * 256 + ((c & 7) * 4 + (j >> 1)) * 8 + ((c >> 3) & 1) * 4 + (j & 1) * 2;
}
__device__ __forceinline__ uint8_t* rec_base(int side, int s, int g, int h) { return (side ? g_vo : g_kq) + (((size_t)s * NSL + g) * NH + h) * REC; }

__global__ void fb_init(const bf16* mem0) {
    for (int i = threadIdx.x; i < CNT_N; i += blockDim.x) g_cnt[i] = i < NSEG ? R_CTAS : 0;
    for (int i = threadIdx.x; i < NMEM * DM; i += blockDim.x) g_fmem[i] = mem0[i];
}
__global__ void fb_weights(const bf16* wq, const bf16* wk, const bf16* wv, const bf16* wo) {
    const int c = blockIdx.x, side = blockIdx.y >> 4, h = blockIdx.y & 15, r = threadIdx.x;
    float acc = 0.f;
    for (int e = 0; e < DHB; e++)
        acc += side == 0 ? bf(wq[(size_t)c * 4096 + h * DHB + e]) * bf(wk[(size_t)r * 4096 + h * DHB + e])
                         : bf(wo[((size_t)h * DHB + e) * DM + c]) * bf(wv[(size_t)r * 4096 + h * DHB + e]);
    if (side == 0) acc *= 0.0625f * 1.4426950408889634f;
    g_fw[(((size_t)side * NH + h) * DM + c) * DM + r] = __float2bfloat16(acc);
}
__global__ void fb_project(const bf16* x, int s_mem) {
    const int g = blockIdx.x / NH, h = blockIdx.x % NH, side = blockIdx.y, s = s_mem >= 0 ? s_mem : blockIdx.z;
    const int nrow = s_mem >= 0 ? NMEM : SEGL;
    const bf16* rows = s_mem >= 0 ? g_fmem : x + (size_t)s * SEGL * DM;
    uint8_t* rec = rec_base(side, s, g, h);
    for (int i = threadIdx.x; i < 64 * nrow; i += blockDim.x) {
        const int c = i / nrow, t = i % nrow;
        const bf16* w = g_fw + (((size_t)side * NH + h) * DM + 64 * g + c) * DM;
        float acc = 0.f;
        for (int r = 0; r < DM; r++) acc += bf(w[r]) * bf(rows[t * DM + r]);
        *reinterpret_cast<bf16*>(rec + (s_mem >= 0 ? rec_mem(side, c, t) : rec_tok(side, c, t))) = __float2bfloat16(acc);
    }
}
__global__ void fb_attend(int s) {
    __shared__ float sc[NMEM * 40];
    const int h = blockIdx.x, i = threadIdx.x / 40, j = threadIdx.x % 40;
    float acc = 0.f;
    for (int c = 0; c < DM; c++) {
        const uint8_t* rec = rec_base(0, s, c >> 6, h);
        acc += bf(g_fmem[i * DM + c]) * bf(*reinterpret_cast<const bf16*>(rec + (j < NMEM ? rec_mem(0, c & 63, j) : rec_tok(0, c & 63, j - NMEM))));
    }
    sc[threadIdx.x] = acc;
    __syncthreads();
    float mx = -INFINITY, sum = 0.f;
    for (int k = 0; k < 40; k++) mx = fmaxf(mx, sc[i * 40 + k]);
    const float e = bf(__float2bfloat16(exp2f(acc - mx)));
    __syncthreads();
    sc[threadIdx.x] = e;
    __syncthreads();
    for (int idx = threadIdx.x; idx < NMEM * DM; idx += blockDim.x) {
        const int ii = idx / DM, c = idx % DM;
        const uint8_t* rec = rec_base(1, s, c >> 6, h);
        float o = 0.f; sum = 0.f;
        for (int k = 0; k < 40; k++) {
            o += sc[ii * 40 + k] * bf(*reinterpret_cast<const bf16*>(rec + (k < NMEM ? rec_mem(1, c & 63, k) : rec_tok(1, c & 63, k - NMEM))));
            sum += sc[ii * 40 + k];
        }
        g_fpart[h * NMEM * DM + idx] = o / sum;
    }
}
__global__ void fb_reduce() {
    const int idx = blockIdx.x * 256 + threadIdx.x;
    float acc = 0.f;
    for (int h = 0; h < NH; h++) acc += g_fpart[h * NMEM * DM + idx];
    g_fmem[idx] = __float2bfloat16(acc);
}

typedef CUresult (*PFN_tmEncode)(CUtensorMap*, CUtensorMapDataType, cuuint32_t, void*, const cuuint64_t*, const cuuint64_t*, const cuuint32_t*, const cuuint32_t*,
                                 CUtensorMapInterleave, CUtensorMapSwizzle, CUtensorMapL2promotion, CUtensorMapFloatOOBfill);
static PFN_tmEncode get_encode() {
    static PFN_tmEncode fn = nullptr;
    if (!fn) {
        void* p = nullptr; cudaDriverEntryPointQueryResult qr;
        cudaGetDriverEntryPoint("cuTensorMapEncodeTiled", &p, cudaEnableDefault, &qr);
        fn = (PFN_tmEncode)p;
    }
    return fn;
}
static void make_map(CUtensorMap* m, const void* base, int rank, const uint64_t* dims, const uint64_t* strides, const uint32_t* box,
                     CUtensorMapSwizzle swz = CU_TENSOR_MAP_SWIZZLE_128B) {
    cuuint64_t d[5], s[5]; cuuint32_t b[5], e[5];
    for (int i = 0; i < rank; i++) { d[i] = dims[i]; b[i] = box[i]; e[i] = 1; }
    for (int i = 0; i + 1 < rank; i++) s[i] = strides[i];
    get_encode()(m, CU_TENSOR_MAP_DATA_TYPE_BFLOAT16, rank, const_cast<void*>(base), d, s, b, e, CU_TENSOR_MAP_INTERLEAVE_NONE, swz,
                 CU_TENSOR_MAP_L2_PROMOTION_L2_256B, CU_TENSOR_MAP_FLOAT_OOB_FILL_NONE);
}

struct HostState { RParams rp; BParams bp; int nb; bool ready, fast; };
static HostState g_host;

static void setup_host(void* const* d_in, void* d_out) {
    const void* x = d_in[0]; const void* wqkv = d_in[1]; const void* awo = d_in[2];
    const void* mem0 = d_in[4]; const void* wq = d_in[5]; const void* wk = d_in[6]; const void* wv = d_in[7]; const void* wo = d_in[8];
    const void* gate = d_in[10];
    RParams& r = g_host.rp; BParams& b = g_host.bp;
    { uint64_t d[2] = {4096, 448}, s[1] = {8192}; uint32_t bx[2] = {64, 64};
      make_map(&r.wq, wq, 2, d, s, bx); make_map(&r.wk, wk, 2, d, s, bx); make_map(&r.wv, wv, 2, d, s, bx); }
    { uint64_t d[2] = {448, 4096}, s[1] = {896}; uint32_t bx[2] = {64, 64}; make_map(&r.wo, wo, 2, d, s, bx); }
    { uint64_t d[3] = {64, 2048, 7}, s[2] = {896, 128}; uint32_t bx[3] = {64, 32, 7}; make_map(&r.x, x, 3, d, s, bx); b.xseg = r.x; }
    r.mem0 = (const bf16*)mem0;
    void *qkv, *o;
    cudaGetSymbolAddress(&qkv, g_qkv); cudaGetSymbolAddress(&o, g_o);
    { uint64_t d[2] = {448, 2048}, s[1] = {896}; uint32_t bx[2] = {64, 128}, bh[2] = {64, 64}; make_map(&b.x64, x, 2, d, s, bh); make_map(&b.o128, o, 2, d, s, bx); }
    { uint64_t d[2] = {1344, 448}, s[1] = {2688}; uint32_t bx[2] = {64, 64}; make_map(&b.wqkv, wqkv, 2, d, s, bx); }
    { uint64_t d[2] = {448, 448}, s[1] = {896}; uint32_t bx[2] = {64, 64}; make_map(&b.wo, awo, 2, d, s, bx); }
    { uint64_t d[2] = {1344, 2048}, s[1] = {2688}; uint32_t bx[2] = {64, 128}; make_map(&b.qkv, qkv, 2, d, s, bx); }
    b.gate_w = (const bf16*)gate; b.x = (const bf16*)x; b.out = (bf16*)d_out;
}

static void launch_all(void* const* d_in, void* d_out, cudaStream_t stream, int att_delay, int att_gap, int tok_delay, int sc_delay) {
    cudaLaunchConfig_t rc = {};
    cudaLaunchAttribute rat[1];
    rat[0].id = cudaLaunchAttributeClusterDimension; rat[0].val.clusterDim.x = R_CS; rat[0].val.clusterDim.y = 1; rat[0].val.clusterDim.z = 1;
    rc.gridDim = dim3(R_CTAS); rc.blockDim = dim3(384); rc.dynamicSmemBytes = R_SMEM; rc.stream = stream; rc.attrs = rat; rc.numAttrs = 1;
    if (!g_host.ready) {
        cudaFuncSetAttribute(r_kernel, cudaFuncAttributeMaxDynamicSharedMemorySize, R_SMEM);
        cudaFuncSetAttribute(r_kernel, cudaFuncAttributeNonPortableClusterSizeAllowed, 1);
        cudaFuncSetAttribute(b_kernel, cudaFuncAttributeMaxDynamicSharedMemorySize, B_SMEM);
        int dev = 0, sms = 0, ncl = 0;
        cudaGetDevice(&dev);
        cudaDeviceGetAttribute(&sms, cudaDevAttrMultiProcessorCount, dev);
        if (cudaOccupancyMaxActiveClusters(&ncl, r_kernel, &rc) != cudaSuccess) { ncl = 0; (void)cudaGetLastError(); }
        g_host.fast = ncl >= NSL && sms - R_CTAS >= 4;
        g_host.nb = g_host.fast ? sms - R_CTAS : sms;
        g_host.ready = true;
    }
    setup_host(d_in, d_out);
    g_host.rp.att_delay = att_delay; g_host.rp.att_gap = att_gap; g_host.rp.tok_delay = tok_delay; g_host.rp.sc_delay = sc_delay;
    g_host.bp.np = g_host.nb >= 18 ? NP_CTAS : (g_host.nb + 3) / 4;
    cudaLaunchConfig_t bc = {};
    cudaLaunchAttribute bat[1];
    bc.gridDim = dim3(g_host.nb); bc.blockDim = dim3(384); bc.dynamicSmemBytes = B_SMEM; bc.stream = stream;
    if (g_host.fast) {
        cudaLaunchKernelEx(&rc, r_kernel, g_host.rp);
        bat[0].id = cudaLaunchAttributeProgrammaticStreamSerialization; bat[0].val.programmaticStreamSerializationAllowed = 1;
        bc.attrs = bat; bc.numAttrs = 1;
    } else {
        const bf16* x = (const bf16*)d_in[0];
        fb_init<<<1, 256, 0, stream>>>((const bf16*)d_in[4]);
        fb_weights<<<dim3(DM, 32), DM, 0, stream>>>((const bf16*)d_in[5], (const bf16*)d_in[6], (const bf16*)d_in[7], (const bf16*)d_in[8]);
        fb_project<<<dim3(R_CTAS, 2, NSEG), 256, 0, stream>>>(x, -1);
        for (int s = 0; s < NSEG; s++) {
            fb_project<<<dim3(R_CTAS, 2, 1), 256, 0, stream>>>(x, s);
            if (s + 1 < NSEG) { fb_attend<<<NH, 320, 0, stream>>>(s); fb_reduce<<<14, 256, 0, stream>>>(); }
        }
    }
    cudaLaunchKernelEx(&bc, b_kernel, g_host.bp);
}

extern "C" void kernel_launch(void* const* d_in, const int* in_sizes, int n_in, void* d_out, int out_size) {
    (void)in_sizes; (void)n_in; (void)out_size;
    launch_all(d_in, d_out, cudaStreamPerThread, 250, 250, 300, 350);
}
```
